```python
import torch

def _softmax(x, axis=-1):
    return torch.softmax(x, dim=axis)
def _gelu(x):
    return torch.nn.functional.gelu(x, approximate="tanh")
def _silu(x):
    return torch.nn.functional.silu(x)
def _sigmoid(x):
    return torch.sigmoid(x)
def _layernorm(x, axis=-1, eps=1e-5):
    m = x.mean(dim=axis, keepdim=True)
    v = x.var(dim=axis, keepdim=True, unbiased=False)
    return (x - m) / torch.sqrt(v + eps)
def _scatter_add(tgt, idx, src, axis=0):
    return tgt.clone().index_add_(axis, idx, src)
def _segment_sum(src, seg, n):
    out = torch.zeros((n,) + src.shape[1:], dtype=src.dtype)
    return out.index_add_(0, seg, src)
def _pad(x, pw):
    flat = tuple(v for pair in reversed(pw) for v in pair)
    return torch.nn.functional.pad(x, flat)

kernel_name = 'concat_heads__gqa_block_cached__mha_block_cached__near_ridge'

def setup_inputs():

    _w = (lambda a: (lambda t: t.to(torch.bfloat16) if t.is_floating_point() else t)(torch.as_tensor(a)))
    def _A_setup():
        B, Sq, D = 16, 96, 640
        Hq, Hkv, Sk, Dh = 32, 32, 512, 128
        assert Hq % Hkv == 0, (Hq, Hkv)
        return {
            "x": _w((lambda *s: torch.randn(*s, dtype=torch.bfloat16) * 0.8)(B, Sq, D)),
            "k_cache": _w((lambda *s: torch.randn(*s, dtype=torch.bfloat16) * 0.8)(B, Hkv, Sk, Dh)),
            "v_cache": _w((lambda *s: torch.randn(*s, dtype=torch.bfloat16) * 0.05)(B, Hkv, Sk, Dh)),
            "wq": _w((lambda *s: torch.randn(*s, dtype=torch.bfloat16) * 0.8)(D, Hq * Dh) * (D ** -0.5)),
            "wo": _w((lambda *s: torch.randn(*s, dtype=torch.bfloat16) * 0.05)(Hq * Dh, D) * ((Hq * Dh) ** -0.5)),
        }
    _A_in = _A_setup()

    def _B_setup():
        B, Sq, D = 16, 96, 640
        H, Sk, Dh = 32, 512, 128
        return {
            "x": _w((lambda *s: torch.randn(*s, dtype=torch.bfloat16) * 0.8)(B, Sq, D)),
            "k_cache": _w((lambda *s: torch.randn(*s, dtype=torch.bfloat16) * 0.8)(B, H, Sk, Dh)),
            "v_cache": _w((lambda *s: torch.randn(*s, dtype=torch.bfloat16) * 0.05)(B, H, Sk, Dh)),
            "wq": _w((lambda *s: torch.randn(*s, dtype=torch.bfloat16) * 0.8)(D, H * Dh) * (D ** -0.5)),
            "wo": _w((lambda *s: torch.randn(*s, dtype=torch.bfloat16) * 0.05)(H * Dh, D) * ((H * Dh) ** -0.5)),
        }
    _B_in = _B_setup()

    return {
        "A_x": _A_in["x"],
        "A_k_cache": _A_in["k_cache"],
        "A_v_cache": _A_in["v_cache"],
        "A_wq": _A_in["wq"],
        "A_wo": _A_in["wo"],
        "B_x": _B_in["x"],
        "B_k_cache": _B_in["k_cache"],
        "B_v_cache": _B_in["v_cache"],
        "B_wq": _B_in["wq"],
        "B_wo": _B_in["wo"],
    }

def reference(A_x, A_k_cache, A_v_cache, A_wq, A_wo, B_x, B_k_cache, B_v_cache, B_wq, B_wo):
    def _A_ref(x, k_cache, v_cache, wq, wo):
        B, Sq, D = x.shape
        Hq, Dh = 32, 128
        Hkv = k_cache.shape[1]
        rep = Hq // Hkv
        q = (lambda x, *d: x.permute(*d))((x @ wq).reshape(B, Sq, Hq, Dh), 0, 2, 1, 3)
        k = (lambda x, n, axis: torch.repeat_interleave(x, n, dim=axis))(k_cache, rep, axis=1)
        v = (lambda x, n, axis: torch.repeat_interleave(x, n, dim=axis))(v_cache, rep, axis=1)
        scores = torch.einsum("bhqd,bhkd->bhqk", q, k) * (Dh ** -0.5)
        p = _softmax(scores, axis=-1)
        o = torch.einsum("bhqk,bhkd->bhqd", p, v)
        return (lambda x, *d: x.permute(*d))(o, 0, 2, 1, 3).reshape(B, Sq, Hq * Dh) @ wo

    def _B_ref(x, k_cache, v_cache, wq, wo):
        B, Sq, D = x.shape
        H, Dh = 32, 128
        q = (lambda x, *d: x.permute(*d))((x @ wq).reshape(B, Sq, H, Dh), 0, 2, 1, 3)
        scores = torch.einsum("bhqd,bhkd->bhqk", q, k_cache) * (Dh ** -0.5)
        p = _softmax(scores, axis=-1)
        o = torch.einsum("bhqk,bhkd->bhqd", p, v_cache)
        return (lambda x, *d: x.permute(*d))(o, 0, 2, 1, 3).reshape(B, Sq, H * Dh) @ wo

    a = _A_ref(A_x, A_k_cache, A_v_cache, A_wq, A_wo)
    b = _B_ref(B_x, B_k_cache, B_v_cache, B_wq, B_wo)
    return torch.concatenate([a, b], axis=-1)
```

```cpp
#include <cuda_runtime.h>
#include <cuda_bf16.h>
#include <cuda.h>
#include <stdint.h>

#define S_SPLIT 4
#define CAP_K 3
#define CAP_V 3
#define PF_INIT 0
#define PF_GAP 300
#define PF_RATE 7
#define EARLY_PF 1
#define PROBE_N 3
#define KRING 8
#define ATT_CL 16
#define AWARE 3
namespace {

constexpr int NB = 16, SQ = 96, DM = 640, NH = 32, SK = 512, DH = 128;
constexpr int RING_H = KRING;
constexpr int IMG = 24576;
constexpr int KSTEP = 3072;
constexpr int NTHREADS = 512;
constexpr int FLAG_STRIDE = 8;
constexpr int TILE_SPAN = 65536;
constexpr int N_PAGES = 2 * RING_H * NB * TILE_SPAN / (1 << 21);
static_assert(N_PAGES <= 16 && (RING_H & (RING_H - 1)) == 0, "");

constexpr int UNIT = 16384;
constexpr int PUNIT = 4 * KSTEP;
constexpr int NP = 4;
constexpr int ATT_K = 0;
constexpr int ATT_V = 4 * UNIT;
constexpr int ATT_Q = 8 * UNIT;
constexpr int ATT_P = ATT_Q + 2 * IMG;
constexpr int ATT_MX = ATT_P + NP * PUNIT;
constexpr int ATT_LINV = ATT_MX + 384;
constexpr int ATT_LP = ATT_LINV + 384;
constexpr int GQ_STAGE = 16384 + 12288;
constexpr int GO_STAGE = 20480 + 2 * KSTEP;
constexpr int G_Q = 0;
constexpr int G_O = 4 * GQ_STAGE;
constexpr int MISC = 231744;
constexpr int MISC_BAR = 231936;
constexpr int SMEM_BYTES = MISC_BAR + 512;
static_assert(ATT_LP + 1536 <= MISC, "");
static_assert(G_O + 4 * GO_STAGE <= MISC, "");

constexpr int B_FULL = 0;
constexpr int B_EMPTY = 8;
constexpr int B_QF = 16;
constexpr int B_FULL2 = 48;
constexpr int B_EMPTY2 = 56;
constexpr int B_GQF = 32;
constexpr int B_GQE = 36;
constexpr int B_GOF = 40;
constexpr int B_GOE = 44;
constexpr int NB_QE = 0, NB_WG0 = 1, NB_MX = 2, NB_L = 3, NB_WG2 = 4, NB_WG2R = 5, NB_L0 = 6, NB_IO = 7, NB_PF = 8  , NB_PE = 12  ;
constexpr int NB_GSLOT = 1, NB_GDONE = 2, NB_GEPI = 3, NB_GWG = 4  ;

enum { ROLE_ATT = 0, ROLE_G = 1, ROLE_NONE = 2 };

struct Params {
  CUtensorMap x[2], wq[2], k[2], v[2], wo[2], out;
  const __nv_bfloat16* kp[2]; const __nv_bfloat16* vp[2];
  int n_clusters, half;
  int n_att, n_local, items_base, items_extra;
  uint32_t hi_sw, hi_sw2, hi_img;
  unsigned char role[40], idx[40];
};

__device__ unsigned char g_scratch_raw[(size_t)(N_PAGES + 1) << 21];
__device__ __align__(128) unsigned char g_qsave[144 * IMG];
__device__ uint32_t g_qflag[2 * RING_H * NB * FLAG_STRIDE];
__device__ uint32_t g_oflag[2 * RING_H * NB * FLAG_STRIDE];
__device__ uint32_t g_odone[2 * NB * 2 * FLAG_STRIDE];
__device__ uint32_t g_side[96];
__device__ uint32_t g_epoch[144 * FLAG_STRIDE];
#define PROF(i) do {} while (0)
#define PROFV(i, v) do {} while (0)
#define ACC_DECL
#define ACC(i) do {} while (0)
#define ACC_OUT(c, base) do {} while (0)

__device__ __forceinline__ long long globaltimer_ns() { long long t; asm volatile("mov.u64 %0, %%globaltimer;" : "=l"(t)); return t; }
__device__ __forceinline__ bool elect_one() {
  uint32_t r;
  asm volatile("{.reg .pred p; elect.sync _|p, 0xffffffff; selp.u32 %0, 1, 0, p;}" : "=r"(r));
  return r;
}
__device__ __forceinline__ uint32_t smem_u32(const void* p) { return (uint32_t)__cvta_generic_to_shared(p); }
__device__ __forceinline__ void mbar_init(uint32_t bar, uint32_t cnt) {
  asm volatile("mbarrier.init.shared::cta.b64 [%0], %1;" ::"r"(bar), "r"(cnt) : "memory");
}
__device__ __forceinline__ void mbar_expect_tx(uint32_t bar, uint32_t bytes) {
  asm volatile("mbarrier.arrive.expect_tx.shared::cta.b64 _, [%0], %1;" ::"r"(bar), "r"(bytes) : "memory");
}
__device__ __forceinline__ void mbar_arrive(uint32_t bar) {
  asm volatile("mbarrier.arrive.shared::cta.b64 _, [%0];" ::"r"(bar) : "memory");
}
__device__ __forceinline__ void mbar_arrive_cluster(uint32_t bar, uint32_t cta) {
  asm volatile("{.reg .b32 ra; mapa.shared::cluster.u32 ra, %0, %1; mbarrier.arrive.shared::cluster.b64 _, [ra];}"
               ::"r"(bar), "r"(cta) : "memory");
}
__device__ __forceinline__ bool mbar_try(uint32_t bar, uint32_t parity) {
  uint32_t ok;
  asm volatile("{.reg .pred p; mbarrier.try_wait.parity.shared::cta.b64 p, [%1], %2; selp.u32 %0, 1, 0, p;}"
               : "=r"(ok) : "r"(bar), "r"(parity) : "memory");
  return ok;
}
__device__ __forceinline__ bool mbar_test(uint32_t bar, uint32_t parity) {
  uint32_t ok;
  asm volatile("{.reg .pred p; mbarrier.test_wait.parity.shared::cta.b64 p, [%1], %2; selp.u32 %0, 1, 0, p;}"
               : "=r"(ok) : "r"(bar), "r"(parity) : "memory");
  return ok;
}
__device__ __forceinline__ void die() { asm volatile("st.global.u32 [%0], %1;" ::"l"(0ull), "r"(0u) : "memory"); }
__device__ __forceinline__ bool mbar_try_long(uint32_t bar, uint32_t parity) {
  uint32_t ok;
  asm volatile("{.reg .pred p; mbarrier.try_wait.parity.shared::cta.b64 p, [%1], %2, %3; selp.u32 %0, 1, 0, p;}"
               : "=r"(ok) : "r"(bar), "r"(parity), "r"(2000u) : "memory");
  return ok;
}
__device__ __forceinline__ void mbar_wait_slow(uint32_t bar, uint32_t parity) {
  uint32_t it = 0;
#pragma unroll 1
  while (!mbar_try_long(bar, parity)) { if (++it > (1u << 22)) { die(); break; } }
}
__device__ __forceinline__ void mbar_wait(uint32_t bar, uint32_t parity) {
  if (__builtin_expect(!mbar_try(bar, parity), 0)) mbar_wait_slow(bar, parity);
}
__device__ __forceinline__ void mbar_wait_lazy(uint32_t bar, uint32_t parity, uint32_t ns) {
  uint32_t it = 0;
#pragma unroll 1
  while (!__all_sync(0xffffffffu, mbar_test(bar, parity))) { if (++it > (1u << 22)) { die(); break; } __nanosleep(ns); }
}
__device__ __forceinline__ void mbar_wait_slow_w(uint32_t bar, uint32_t parity) {
  uint32_t it = 0;
#pragma unroll 1
  while (!__all_sync(0xffffffffu, mbar_try_long(bar, parity))) { if (++it > (1u << 22)) { die(); break; } }
}
__device__ __forceinline__ void mbar_wait_w(uint32_t bar, uint32_t parity) {
  if (__builtin_expect(!__all_sync(0xffffffffu, mbar_try(bar, parity)), 0)) mbar_wait_slow_w(bar, parity);
}
__device__ __forceinline__ uint32_t ld_acquire(const uint32_t* p) {
  uint32_t v; asm volatile("ld.acquire.gpu.global.u32 %0, [%1];" : "=r"(v) : "l"(p) : "memory"); return v;
}
__device__ __forceinline__ void st_release(uint32_t* p, uint32_t v) {
  asm volatile("st.release.gpu.global.u32 [%0], %1;" ::"l"(p), "r"(v) : "memory");
}
__device__ __forceinline__ uint32_t flag_wait(const uint32_t* p, uint32_t seq) {
  uint32_t it = 0, v;
#pragma unroll 1
  while (v = ld_acquire(p), !__all_sync(0xffffffffu, (int32_t)(v - (seq << 1)) >= 0)) {
    if (++it > (1u << 22)) { die(); break; }
    __nanosleep(20);
  }
  return __shfl_sync(0xffffffffu, v, 0) & 1;
}
__device__ __forceinline__ void st_relaxed(uint32_t* p, uint32_t v) {
  asm volatile("st.relaxed.gpu.global.u32 [%0], %1;" ::"l"(p), "r"(v) : "memory");
}
__device__ __forceinline__ void fence_async_global() { asm volatile("fence.proxy.async.global;" ::: "memory"); }
__device__ __forceinline__ void fence_async_smem() { asm volatile("fence.proxy.async.shared::cta;" ::: "memory"); }

__device__ __forceinline__ void bulk_load(uint32_t dst, const void* src, uint32_t bytes, uint32_t bar) {
  asm volatile("cp.async.bulk.shared::cluster.global.mbarrier::complete_tx::bytes [%0], [%1], %2, [%3];"
               ::"r"(dst), "l"(src), "r"(bytes), "r"(bar) : "memory");
}
__device__ __forceinline__ void bulk_store(void* dst, uint32_t src, uint32_t bytes) {
  asm volatile("cp.async.bulk.global.shared::cta.bulk_group [%0], [%1], %2;" ::"l"(dst), "r"(src), "r"(bytes) : "memory");
}
__device__ __forceinline__ void tma2d_store(const CUtensorMap* m, int c0, int c1, uint32_t src) {
  asm volatile("cp.async.bulk.tensor.2d.global.shared::cta.bulk_group [%0, {%1, %2}], [%3];"
               ::"l"(m), "r"(c0), "r"(c1), "r"(src) : "memory");
}
__device__ __forceinline__ void bulk_commit() { asm volatile("cp.async.bulk.commit_group;" ::: "memory"); }
__device__ __forceinline__ void bulk_wait_read() { asm volatile("cp.async.bulk.wait_group.read 0;" ::: "memory"); }
__device__ __forceinline__ void bulk_wait_all() { asm volatile("cp.async.bulk.wait_group 0;" ::: "memory"); }
__device__ __forceinline__ void tma2d(uint32_t dst, const CUtensorMap* m, int c0, int c1, uint32_t bar, uint64_t pol) {
  asm volatile("cp.async.bulk.tensor.2d.shared::cluster.global.mbarrier::complete_tx::bytes.L2::cache_hint [%0], [%1, {%3, %4}], [%2], %5;"
               ::"r"(dst), "l"(m), "r"(bar), "r"(c0), "r"(c1), "l"(pol) : "memory");
}
__device__ __forceinline__ void tma2d_mc(uint32_t dst, const CUtensorMap* m, int c0, int c1, uint32_t bar, uint64_t pol) {
  asm volatile("cp.async.bulk.tensor.2d.shared::cluster.global.mbarrier::complete_tx::bytes.multicast::cluster.L2::cache_hint [%0], [%1, {%3, %4}], [%2], %5, %6;"
               ::"r"(dst), "l"(m), "r"(bar), "r"(c0), "r"(c1), "h"((uint16_t)3), "l"(pol) : "memory");
}
__device__ __forceinline__ void tma3d(uint32_t dst, const CUtensorMap* m, int c0, int c1, int c2, uint32_t bar, uint64_t pol) {
  asm volatile("cp.async.bulk.tensor.3d.shared::cluster.global.mbarrier::complete_tx::bytes.L2::cache_hint [%0], [%1, {%3, %4, %5}], [%2], %6;"
               ::"r"(dst), "l"(m), "r"(bar), "r"(c0), "r"(c1), "r"(c2), "l"(pol) : "memory");
}
__device__ __forceinline__ void tma3d_mc(uint32_t dst, const CUtensorMap* m, int c0, int c1, int c2, uint32_t bar, uint64_t pol) {
  asm volatile("cp.async.bulk.tensor.3d.shared::cluster.global.mbarrier::complete_tx::bytes.multicast::cluster.L2::cache_hint [%0], [%1, {%3, %4, %5}], [%2], %6, %7;"
               ::"r"(dst), "l"(m), "r"(bar), "r"(c0), "r"(c1), "r"(c2), "h"((uint16_t)3), "l"(pol) : "memory");
}
__device__ __forceinline__ void tma2d_prefetch(const CUtensorMap* m, int c0, int c1, uint64_t pol) {
  asm volatile("cp.async.bulk.prefetch.tensor.2d.L2.global.L2::cache_hint [%0, {%1, %2}], %3;"
               ::"l"(m), "r"(c0), "r"(c1), "l"(pol) : "memory");
}
__device__ __forceinline__ void tma3d_prefetch(const CUtensorMap* m, int c0, int c1, int c2, uint64_t pol) {
  asm volatile("cp.async.bulk.prefetch.tensor.3d.L2.global.L2::cache_hint [%0, {%1, %2, %3}], %4;"
               ::"l"(m), "r"(c0), "r"(c1), "r"(c2), "l"(pol) : "memory");
}
__device__ __forceinline__ uint64_t policy_evict_normal() {
  uint64_t p; asm volatile("createpolicy.fractional.L2::evict_normal.b64 %0, 1.0;" : "=l"(p)); return p;
}
__device__ __forceinline__ uint64_t policy_evict_first() {
  uint64_t p; asm volatile("createpolicy.fractional.L2::evict_first.b64 %0, 1.0;" : "=l"(p)); return p;
}

__device__ __forceinline__ void wg_fence() { asm volatile("wgmma.fence.sync.aligned;" ::: "memory"); }
__device__ __forceinline__ void wg_commit() { asm volatile("wgmma.commit_group.sync.aligned;" ::: "memory"); }
template <int N> __device__ __forceinline__ void wg_wait() { asm volatile("wgmma.wait_group.sync.aligned %0;" ::"n"(N) : "memory"); }
__device__ __forceinline__ void reg_fence(float (&d)[48]) {
#pragma unroll
  for (int i = 0; i < 48; i++) asm volatile("" : "+f"(d[i])::"memory");
}

constexpr uint32_t SW128_HI = (1u << 30) | (1024 >> 4), SW128_LO = 1u << 16;
constexpr uint32_t IMG_HI = 128 >> 4, IMG_LO = (1536 >> 4) << 16;
__device__ __forceinline__ uint32_t desc_sw128(uint32_t addr) { return SW128_LO | ((addr & 0x3FFFF) >> 4); }
__device__ __forceinline__ uint32_t desc_img(uint32_t addr) { return IMG_LO | ((addr & 0x3FFFF) >> 4); }

struct DescHi { uint32_t sw, sw2, img; };
template <int TA, int TB>
__device__ __forceinline__ void wgmma96(float (&d)[48], uint32_t da, uint32_t db, int scale_d, const DescHi& hi) {
  asm volatile(
      "{.reg .pred p; .reg .b64 da, db; setp.ne.b32 p, %50, 0; mov.b64 da, {%48, %53}; mov.b64 db, {%49, %54};\n"
      "wgmma.mma_async.sync.aligned.m64n96k16.f32.bf16.bf16 "
      "{%0,%1,%2,%3,%4,%5,%6,%7,%8,%9,%10,%11,%12,%13,%14,%15,%16,%17,%18,%19,%20,%21,%22,%23,%24,%25,%26,%27,%28,%29,%30,%31,%32,%33,%34,%35,%36,%37,%38,%39,%40,%41,%42,%43,%44,%45,%46,%47},"
      " da, db, p, 1, 1, %51, %52;}\n"
      : "+f"(d[0]), "+f"(d[1]), "+f"(d[2]), "+f"(d[3]), "+f"(d[4]), "+f"(d[5]), "+f"(d[6]), "+f"(d[7]), "+f"(d[8]), "+f"(d[9]), "+f"(d[10]), "+f"(d[11]), "+f"(d[12]), "+f"(d[13]), "+f"(d[14]), "+f"(d[15]), "+f"(d[16]), "+f"(d[17]), "+f"(d[18]), "+f"(d[19]), "+f"(d[20]), "+f"(d[21]), "+f"(d[22]), "+f"(d[23]), "+f"(d[24]), "+f"(d[25]), "+f"(d[26]), "+f"(d[27]), "+f"(d[28]), "+f"(d[29]), "+f"(d[30]), "+f"(d[31]), "+f"(d[32]), "+f"(d[33]), "+f"(d[34]), "+f"(d[35]), "+f"(d[36]), "+f"(d[37]), "+f"(d[38]), "+f"(d[39]), "+f"(d[40]), "+f"(d[41]), "+f"(d[42]), "+f"(d[43]), "+f"(d[44]), "+f"(d[45]), "+f"(d[46]), "+f"(d[47])
      : "r"(da), "r"(db), "r"(scale_d), "n"(TA), "n"(TB), "r"(hi.sw), "r"(TB ? hi.img : hi.sw2));
}
template <int TA, int TB>
__device__ __forceinline__ void wgmma96_first(float (&d)[48], uint32_t da, uint32_t db, const DescHi& hi) {
  asm volatile(
      "{.reg .pred p; .reg .b64 da, db; setp.ne.b32 p, 0, 0; mov.b64 da, {%48, %52}; mov.b64 db, {%49, %53};\n"
      "wgmma.mma_async.sync.aligned.m64n96k16.f32.bf16.bf16 "
      "{%0,%1,%2,%3,%4,%5,%6,%7,%8,%9,%10,%11,%12,%13,%14,%15,%16,%17,%18,%19,%20,%21,%22,%23,%24,%25,%26,%27,%28,%29,%30,%31,%32,%33,%34,%35,%36,%37,%38,%39,%40,%41,%42,%43,%44,%45,%46,%47},"
      " da, db, p, 1, 1, %50, %51;}\n"
      : "=f"(d[0]), "=f"(d[1]), "=f"(d[2]), "=f"(d[3]), "=f"(d[4]), "=f"(d[5]), "=f"(d[6]), "=f"(d[7]), "=f"(d[8]), "=f"(d[9]), "=f"(d[10]), "=f"(d[11]), "=f"(d[12]), "=f"(d[13]), "=f"(d[14]), "=f"(d[15]), "=f"(d[16]), "=f"(d[17]), "=f"(d[18]), "=f"(d[19]), "=f"(d[20]), "=f"(d[21]), "=f"(d[22]), "=f"(d[23]), "=f"(d[24]), "=f"(d[25]), "=f"(d[26]), "=f"(d[27]), "=f"(d[28]), "=f"(d[29]), "=f"(d[30]), "=f"(d[31]), "=f"(d[32]), "=f"(d[33]), "=f"(d[34]), "=f"(d[35]), "=f"(d[36]), "=f"(d[37]), "=f"(d[38]), "=f"(d[39]), "=f"(d[40]), "=f"(d[41]), "=f"(d[42]), "=f"(d[43]), "=f"(d[44]), "=f"(d[45]), "=f"(d[46]), "=f"(d[47])
      : "r"(da), "r"(db), "n"(TA), "n"(TB), "r"(hi.sw), "r"(TB ? hi.img : hi.sw2));
}

__device__ __forceinline__ uint32_t pack_bf16(float lo, float hi) {
  uint32_t r; asm("cvt.rn.bf16x2.f32 %0, %1, %2;" : "=r"(r) : "f"(hi), "f"(lo)); return r;
}
__device__ __forceinline__ float ex2(float x) { float y; asm("ex2.approx.ftz.f32 %0, %1;" : "=f"(y) : "f"(x)); return y; }
__device__ __forceinline__ void stsm4(uint32_t addr, uint32_t a, uint32_t b, uint32_t c, uint32_t d) {
  asm volatile("stmatrix.sync.aligned.m8n8.x4.shared.b16 [%0], {%1,%2,%3,%4};" ::"r"(addr), "r"(a), "r"(b), "r"(c), "r"(d) : "memory");
}
__device__ __forceinline__ void stsm4_t(uint32_t addr, uint32_t a, uint32_t b, uint32_t c, uint32_t d) {
  asm volatile("stmatrix.sync.aligned.m8n8.x4.trans.shared.b16 [%0], {%1,%2,%3,%4};" ::"r"(addr), "r"(a), "r"(b), "r"(c), "r"(d) : "memory");
}
template <int N> __device__ __forceinline__ void bar_sync(int id) { asm volatile("bar.sync %0, %1;" ::"r"(id), "n"(N) : "memory"); }
template <int N> __device__ __forceinline__ void bar_arrive(int id) { asm volatile("bar.arrive %0, %1;" ::"r"(id), "n"(N) : "memory"); }
__device__ __forceinline__ bool bar_or128(int id, bool v) {
  uint32_t r;
  asm volatile("{.reg .pred p, q; setp.ne.b32 p, %2, 0; bar.red.or.pred q, %1, 128, p; selp.u32 %0, 1, 0, q;}"
               : "=r"(r) : "r"(id), "r"((uint32_t)v) : "memory");
  return r;
}
__device__ __forceinline__ void sts32(uint32_t addr, uint32_t v) { asm volatile("st.shared.u32 [%0], %1;" ::"r"(addr), "r"(v) : "memory"); }
__device__ __forceinline__ uint32_t lds32(uint32_t addr) { uint32_t v; asm volatile("ld.shared.u32 %0, [%1];" : "=r"(v) : "r"(addr) : "memory"); return v; }
__device__ __forceinline__ float2 lds64f(uint32_t addr) {
  float2 v; asm volatile("ld.shared.v2.f32 {%0,%1}, [%2];" : "=f"(v.x), "=f"(v.y) : "r"(addr) : "memory"); return v;
}
template <bool IS_MAX>
__device__ __forceinline__ void col_reduce(const float (&v)[24], float (&r)[3], int lane) {
  float a[12], b[6];
  const bool h16 = lane & 16, h8 = lane & 8, h4 = lane & 4;
#pragma unroll
  for (int i = 0; i < 12; i++) {
    float keep = h16 ? v[12 + i] : v[i], send = h16 ? v[i] : v[12 + i];
    float o = __shfl_xor_sync(0xffffffffu, send, 16);
    a[i] = IS_MAX ? fmaxf(keep, o) : keep + o;
  }
#pragma unroll
  for (int i = 0; i < 6; i++) {
    float keep = h8 ? a[6 + i] : a[i], send = h8 ? a[i] : a[6 + i];
    float o = __shfl_xor_sync(0xffffffffu, send, 8);
    b[i] = IS_MAX ? fmaxf(keep, o) : keep + o;
  }
#pragma unroll
  for (int i = 0; i < 3; i++) {
    float keep = h4 ? b[3 + i] : b[i], send = h4 ? b[i] : b[3 + i];
    float o = __shfl_xor_sync(0xffffffffu, send, 4);
    r[i] = IS_MAX ? fmaxf(keep, o) : keep + o;
  }
}
__device__ __forceinline__ int col_of(int lane, int i) {
  int c = 12 * ((lane >> 4) & 1) + 6 * ((lane >> 3) & 1) + 3 * ((lane >> 2) & 1) + i;
  return 8 * (c >> 1) + 2 * (lane & 3) + (c & 1);
}

__device__ __forceinline__ void store_image(unsigned char* dst  , const float (&d)[48]) {
#pragma unroll
  for (int j = 0; j < 12; j++) {
    *reinterpret_cast<uint32_t*>(dst + j * 128) = pack_bf16(d[4 * j], d[4 * j + 1]);
    *reinterpret_cast<uint32_t*>(dst + 1536 + j * 128) = pack_bf16(d[4 * j + 2], d[4 * j + 3]);
  }
}

struct Tid {
  int tid, t, w, warp, lane;
  __device__ __forceinline__ Tid() {
    asm volatile("mov.u32 %0, %%tid.x;" : "=r"(tid));
    const int wi = __shfl_sync(0xffffffffu, tid >> 5, 0);
    t = tid & 127; w = wi >> 2; warp = wi & 3; lane = tid & 31;
  }
};

#define policy_w policy_evict_normal

struct Ctx {
  uint32_t sb;
  int br, idx, rank;
  uint32_t seq0;
  uint32_t pol;
};
__device__ __forceinline__ unsigned char* scratch_base() {
  return reinterpret_cast<unsigned char*>((reinterpret_cast<uintptr_t>(g_scratch_raw) + (1u << 21) - 1) & ~(uintptr_t)((1u << 21) - 1));
}
__device__ __forceinline__ uint32_t chunk_par(uint32_t off) { return ((off >> 12) ^ (off >> 13) ^ (off >> 16) ^ (off >> 17) ^ (off >> 19)) & 1; }
__device__ __forceinline__ int tile_id(int br, int h, int b) { return (br * RING_H + (h & (RING_H - 1))) * NB + b; }
__device__ __forceinline__ uint32_t tile_pol(const Ctx& c, int tile) {
  return (AWARE & 2) ? chunk_par((uint32_t)tile * TILE_SPAN) ^ ((c.pol >> (tile >> 5)) & 1) : 0;
}
__device__ __forceinline__ unsigned char* tile_step(int tile, int k, uint32_t pol) {
  return scratch_base() + (size_t)tile * TILE_SPAN + k * 8192 + ((AWARE & 2) ? (((k & 1) ^ pol) << 12) : 0);
}

template <bool B> struct BoolC { static constexpr bool value = B; };

struct Ring {
  uint32_t s, ph;
  template <int N> __device__ __forceinline__ void next() { if (++s == N) { s = 0; ph ^= 1; } }
};

constexpr float SM_C = 0.08838834764831845f * 1.4426950408889634f;
constexpr float SM_LIMIT = 1099511627776.0f;

__device__ __forceinline__ void att_producer(const Params& p, const Ctx& c, int a, int n_items, int isv) {
  const uint64_t pol = policy_evict_first();
  const uint32_t sb = c.sb, bars = sb + MISC_BAR;
  const CUtensorMap* m = (isv ? p.v : p.k) + c.br;
  const bool local = a < p.n_local;
  if (isv && local) {
    const uint64_t poln = policy_evict_normal(), polw = policy_w();
    const int h = a >> 4, b = a & 15;
#pragma unroll 1
    for (int kc = 0; kc < 10; kc++) {
      const int st = kc & 7;
      if (kc >= 8) mbar_wait_slow_w(bars + 8 * (B_EMPTY2 + st), 0);
      if (elect_one()) {
        const uint32_t wdst = sb + ((st + 4) & 7) * UNIT;
        mbar_expect_tx(bars + 8 * (B_FULL2 + st), 16384 + 12288);
        tma2d(sb + ATT_Q + st * 12288, &p.x[c.br], kc * 64, b * SQ, bars + 8 * (B_FULL2 + st), poln);
        tma2d(wdst, &p.wq[c.br], h * DH, kc * 64, bars + 8 * (B_FULL2 + st), polw);
        tma2d(wdst + 8192, &p.wq[c.br], h * DH + 64, kc * 64, bars + 8 * (B_FULL2 + st), polw);
      }
    }
  }
  auto row_of = [&](int n) {
    const int item = a + n * p.n_att;
    return ((item & 15) * NH + (item >> 4)) * SK;
  };
  int pf = 0;
  auto prefetch = [&]() {
    if (pf < 8 * n_items && elect_one()) tma3d_prefetch(m, 0, row_of(pf >> 3) + 64 * (pf & 7), 0, pol);
    pf++;
  };
  if (local) {
#pragma unroll 1
    for (int i = 0; i < PF_INIT; i++) { prefetch(); __nanosleep(PF_GAP); }
  }
  const uint32_t bar0 = bars + 32 * isv, dst0 = sb + 4 * isv * UNIT;
  for (int n = 0; n < n_items; n++) {
    const int row = row_of(n);
#pragma unroll 1
    for (int u = 0; u < 8; u++) {
      const uint32_t bar = bar0 + 8 * (u & 3);
      if (n == 0 && u < 4 && local) mbar_wait_slow_w(bars + 8 * (B_EMPTY2 + (isv ? u : u + 4)), isv && u < 2);
      mbar_wait_slow_w(bar + 8 * B_EMPTY, (u >> 2) ^ 1);
      const int cap = isv ? CAP_V : CAP_K;
      if (cap < 4 && (n > 0 || u >= cap)) mbar_wait_slow_w(bar0 + 8 * ((u - cap) & 3) + 8 * B_FULL, ((u - cap) >> 2) & 1);
      if (elect_one()) {
        mbar_expect_tx(bar + 8 * B_FULL, UNIT);
        tma3d(dst0 + (u & 3) * UNIT, m, 0, row + 64 * u, 0, bar + 8 * B_FULL, pol);
      }
      if (pf > 8 * n + u + 2 && u < PF_RATE && (n > 0 || u >= 4)) prefetch();
    }
  }
}

__device__ __forceinline__ void att_qloader(const Params& p, const Ctx& c, int a, int n_items) {
  const uint32_t sb = c.sb, bars = sb + MISC_BAR;
  const int lane = threadIdx.x & 31;
  for (int n = a < p.n_local; n < n_items; n++) {
    const int item = a + n * p.n_att, tile = tile_id(c.br, item >> 4, item & 15);
    const uint32_t pl = flag_wait(&g_qflag[tile * FLAG_STRIDE], c.seq0 + (item >> 4));
    fence_async_global();
    if (n >= 2) bar_sync<64>(NB_QE);
    else if (n == 1 && a < p.n_local) mbar_wait_slow_w(bars + 8 * B_QF, 0);
    if (lane == 0) { sts32(sb + MISC + 136 + 4 * (n & 1), pl); mbar_expect_tx(bars + 8 * (B_QF + (n & 1)), IMG); }
    __syncwarp();
    if (lane < 8) bulk_load(sb + ATT_Q + (n & 1) * IMG + lane * KSTEP, tile_step(tile, lane, pl), KSTEP, bars + 8 * (B_QF + (n & 1)));
    __syncwarp();
  }
}

__device__ __forceinline__ void att_storer(const Params& p, const Ctx& c, int a, int n_items) {
  const uint32_t sb = c.sb;
  const int lane = threadIdx.x & 31;
  for (int n = 0; n < n_items; n++) {
    const int item = a + n * p.n_att, tile = tile_id(c.br, item >> 4, item & 15);
    bar_sync<160>(NB_IO);
    if (lane == 0 && (n & 7) == 0) PROF(40 + n);
    const uint32_t pl = (n == 0 && a < p.n_local) ? tile_pol(c, tile) : lds32(sb + MISC + 136 + 4 * (n & 1));
    if (lane < 8) {
      bulk_store(tile_step(tile, lane, pl), sb + ATT_Q + (n & 1) * IMG + lane * KSTEP, KSTEP);
      bulk_commit();
      bulk_wait_read();
    }
    __syncwarp();
    if (lane == 0 && (n & 7) == 0) PROF(41 + n);
    if (n + 2 < n_items) bar_arrive<64>(NB_QE);
    if (lane < 8) bulk_wait_all();
    __syncwarp();
    if (lane == 0 && (n & 7) == 0) PROF(42 + n);
    if (lane == 0) st_release(&g_oflag[tile * FLAG_STRIDE], ((c.seq0 + (item >> 4)) << 1) | pl);
    __syncwarp();
    if (lane == 0 && (n & 7) == 0) PROF(43 + n);
  }
}

__device__ __forceinline__ void att_softmax_wg(const Params& p, uint32_t sb, int n_items) {
  const DescHi hi{p.hi_sw, p.hi_sw2, p.hi_img};
  const Tid T; const int W = T.w, warp = T.warp, lane = T.lane;
  const uint32_t bars = sb + MISC_BAR;
  float s[48], x[48], mc[24], l[24];
  ACC_DECL
  const uint32_t p_st = sb + ATT_P + W * PUNIT + warp * KSTEP + ((lane >> 3) & 1) * 1536 + (lane >> 4) * 128 + (lane & 7) * 16;
  const uint32_t col_off = (lane & 3) * 8;
  const uint32_t kbar = bars + 8 * W;
  const uint32_t kdesc = desc_sw128(sb + ATT_K + W * UNIT), qdesc = desc_img(sb + ATT_Q);
#pragma unroll
  for (int c = 0; c < 24; c++) l[c] = 0.f;

  auto make_ref = [&]() {
    const uint32_t mx = sb + ATT_MX;
    if (W == 0) {
      float v[6];
      auto pick = [&](int j0) {
#pragma unroll
        for (int k = 0; k < 6; k++) v[k] = fmaxf(s[4 * (j0 + (k >> 1)) + (k & 1)], s[4 * (j0 + (k >> 1)) + 2 + (k & 1)]);
      };
      if (warp == 0) pick(0); else if (warp == 1) pick(3); else if (warp == 2) pick(6); else pick(9);
#pragma unroll
      for (int o = 4; o < 32; o <<= 1)
#pragma unroll
        for (int k = 0; k < 6; k++) v[k] = fmaxf(v[k], __shfl_xor_sync(0xffffffffu, v[k], o));
      if (lane < 4) {
#pragma unroll
        for (int k = 0; k < 3; k++)
          asm volatile("st.shared.v2.f32 [%0], {%1, %2};" ::"r"(mx + col_off + warp * 96 + k * 32), "f"(v[2 * k] * SM_C), "f"(v[2 * k + 1] * SM_C) : "memory");
      }
      bar_arrive<256>(NB_MX);
      bar_sync<128>(NB_WG0);
    } else {
      bar_sync<256>(NB_MX);
    }
#pragma unroll
    for (int j = 0; j < 12; j++) { const float2 q = lds64f(mx + col_off + 32 * j); mc[2 * j] = q.x; mc[2 * j + 1] = q.y; }
  };
  auto scale_scores = [&]() {
    reg_fence(s);
#pragma unroll
    for (int c = 0; c < 48; c++) x[c] = fmaf(s[c], SM_C, -mc[2 * (c >> 2) + (c & 1)]);
    reg_fence(x);
  };
  auto exp_store = [&](auto with_s, uint32_t g) {
    constexpr bool WITH_S = decltype(with_s)::value;
    bar_sync<256>(NB_PE + W + 2 * (g & 1));
    const uint32_t dst = p_st + (g & 1) * (2 * PUNIT);
    const uint32_t da = kdesc + ((g + 1) & 1) * (2 * UNIT >> 4);
    const uint32_t db = qdesc + (((g + 1) >> 2) & 1) * (IMG >> 4);
    if (WITH_S) wg_fence();
#pragma unroll
    for (int q = 0; q < 6; q++) {
      if (WITH_S && q < S_SPLIT) {
#pragma unroll
        for (int kk = q * (8 / S_SPLIT); kk < (q + 1) * (8 / S_SPLIT); kk++) {
          if (kk == 0) wgmma96_first<0, 1>(s, da, db, hi);
          else wgmma96<0, 1>(s, da + (((kk >> 2) * 8192 + (kk & 3) * 32) >> 4), db + ((kk * KSTEP) >> 4), 1, hi);
        }
        if (q == S_SPLIT - 1) wg_commit();
      }
      float e[8];
#pragma unroll
      for (int k = 0; k < 8; k++) e[k] = ex2(x[8 * q + k]);
      l[4 * q + 0] += e[0] + e[2];
      l[4 * q + 1] += e[1] + e[3];
      l[4 * q + 2] += e[4] + e[6];
      l[4 * q + 3] += e[5] + e[7];
      stsm4(dst + q * 256, pack_bf16(e[0], e[1]), pack_bf16(e[2], e[3]), pack_bf16(e[4], e[5]), pack_bf16(e[6], e[7]));
    }
  };
  auto publish = [&](uint32_t g) {
    fence_async_smem();
    bar_arrive<256>(NB_PF + W + 2 * (g & 1));
  };
  auto last_unit = [&]() {
    float rr[3];
    col_reduce<false>(l, rr, lane);
    if (W == 1) {
      bar_sync<256>(NB_L0);
#pragma unroll
      for (int k = 0; k < 3; k++) rr[k] += __uint_as_float(lds32(sb + ATT_LP + warp * 384 + 4 * col_of(lane, k)));
    }
#pragma unroll
    for (int k = 0; k < 3; k++) sts32(sb + ATT_LP + warp * 384 + 4 * col_of(lane, k), __float_as_uint(rr[k]));
    bar_arrive<256>(W ? NB_L : NB_L0);
#pragma unroll
    for (int c = 0; c < 24; c++) l[c] = 0.f;
  };

  const uint32_t g_last = 4 * n_items - 1;
  mbar_wait_w(bars + 8 * B_QF, 0);
  mbar_wait_w(kbar + 8 * B_FULL, 0);
  wg_fence();
  wgmma96_first<0, 1>(s, kdesc, qdesc, hi);
#pragma unroll
  for (int kk = 1; kk < 8; kk++)
    wgmma96<0, 1>(s, kdesc + (((kk >> 2) * 8192 + (kk & 3) * 32) >> 4), qdesc + ((kk * KSTEP) >> 4), 1, hi);
  wg_commit();
  wg_wait<0>();
  if (lane == 0) mbar_arrive(kbar + 8 * B_EMPTY);
  if (T.tid == 0) PROF(1);
  reg_fence(s);
  make_ref();
  scale_scores();
  ACC(0);
  bool ready = false;
#pragma unroll 1
  for (uint32_t g = 0; g != g_last; g++) {
    const uint32_t gn = g + 1;
    const uint32_t kb = kbar + 16 * (gn & 1);
    if (__builtin_expect(!__all_sync(0xffffffffu, ready), 0)) {
      if ((gn & 3) == 0) mbar_wait_w(bars + 8 * (B_QF + ((gn >> 2) & 1)), (gn >> 3) & 1);
      ACC(1);
      mbar_wait_w(kb + 8 * B_FULL, (gn >> 1) & 1);
    }
    ACC(2);
    exp_store(BoolC<true>{}, g);
    ready = mbar_test(kbar + 16 * (g & 1) + 8 * B_FULL, ((gn + 1) >> 1) & 1) && (gn & 3) != 3;
    ACC(5);
    if (__builtin_expect((gn & 3) == 0, 0)) {
      publish(g);
      last_unit();
      wg_wait<0>();
      if (lane == 0) mbar_arrive(kb + 8 * B_EMPTY);
      reg_fence(s);
      make_ref();
      scale_scores();
    } else {
      wg_wait<0>();
      if (lane == 0) mbar_arrive(kb + 8 * B_EMPTY);
      scale_scores();
      publish(g);
    }
    ACC(7);
  }
  exp_store(BoolC<false>{}, g_last);
  publish(g_last);
  last_unit();
  ACC_OUT(T.t == 0, W * 16);
}

__device__ __forceinline__ void att_fallback(const __nv_bfloat16* kp, const __nv_bfloat16* vp, const unsigned char* qimg,
                                          uint32_t sb, uint32_t oimg, int q, int t) {
  const uint32_t fq = sb + ATT_LP, fs = fq + 512, fr = fs + 512;
  const uint32_t eoff = (t >> 4) * KSTEP + ((t >> 3) & 1) * 1536 + (q >> 3) * 128 + (t & 7) * 16 + (q & 7) * 2;
  const unsigned short qraw = __ldcg(reinterpret_cast<const unsigned short*>(qimg + eoff));
  sts32(fq + 4 * t, (uint32_t)qraw << 16);
  bar_sync<128>(NB_WG2);
  float sc[4], mx = -INFINITY;
#pragma unroll
  for (int r = 0; r < 4; r++) {
    const __nv_bfloat16* kr = kp + (size_t)(t + 128 * r) * DH;
    float a = 0.f;
#pragma unroll 4
    for (int d = 0; d < DH; d++) a = fmaf(__uint_as_float(lds32(fq + 4 * d)), __bfloat162float(kr[d]), a);
    sc[r] = a * SM_C; mx = fmaxf(mx, sc[r]);
  }
  for (int o = 16; o; o >>= 1) mx = fmaxf(mx, __shfl_xor_sync(0xffffffffu, mx, o));
  if ((t & 31) == 0) sts32(fr + 4 * (t >> 5), __float_as_uint(mx));
  bar_sync<128>(NB_WG2);
  for (int i = 0; i < 4; i++) mx = fmaxf(mx, __uint_as_float(lds32(fr + 4 * i)));
  float sum = 0.f, a = 0.f;
#pragma unroll
  for (int r = 0; r < 4; r++) {
    sts32(fs + 4 * t, __float_as_uint(ex2(sc[r] - mx)));
    bar_sync<128>(NB_WG2);
#pragma unroll 4
    for (int k = 0; k < 128; k++) {
      const float e = __uint_as_float(lds32(fs + 4 * k));
      sum += e;
      a = fmaf(e, __bfloat162float(vp[(size_t)(128 * r + k) * DH + t]), a);
    }
    bar_sync<128>(NB_WG2);
  }
  const unsigned short res = __bfloat16_as_ushort(__float2bfloat16(a / sum));
  asm volatile("st.shared.u16 [%0], %1;" ::"r"(oimg + eoff), "h"(res) : "memory");
  bar_sync<128>(NB_WG2);
}

__device__ __forceinline__ void att_pv_wg(const Params& p, const Ctx& c, int a, int n_items) {
  const uint32_t sb = c.sb;
  const DescHi hi{p.hi_sw, p.hi_sw2, p.hi_img};
  const Tid T; const int t = T.t, warp = T.warp, lane = T.lane;
  const uint32_t bars = sb + MISC_BAR;
  float o[2][48];
  ACC_DECL
  const uint32_t col_off = (lane & 3) * 8;
  const uint32_t o_st = sb + ATT_Q + warp * KSTEP + ((lane >> 3) & 1) * 1536 + (lane >> 4) * 128 + (lane & 7) * 16;
  const uint32_t vdesc = desc_sw128(sb + ATT_V), pdesc = desc_img(sb + ATT_P);
  if (a < p.n_local) {
#pragma unroll 1
    for (int kc = 0; kc < 10; kc++) {
      const int st = kc & 7;
      mbar_wait_w(bars + 8 * (B_FULL2 + st), kc >> 3);
      if (t == 0) PROF(60 + kc);
      const uint32_t da = desc_sw128(sb + ((st + 4) & 7) * UNIT);
      const uint32_t db = desc_sw128(sb + ATT_Q + st * 12288);
      wg_fence();
#pragma unroll
      for (int kk = 0; kk < 4; kk++)
#pragma unroll
        for (int m = 0; m < 2; m++)
          wgmma96<1, 0>(o[m], da + ((m * 8192 + kk * 2048) >> 4), db + ((kk * 32) >> 4), (kc | kk) != 0, hi);
      wg_commit();
      wg_wait<1>();
      if (kc > 0 && lane == 0) mbar_arrive(bars + 8 * (B_EMPTY2 + ((kc - 1) & 7)));
    }
    wg_wait<0>();
    if (lane == 0) mbar_arrive(bars + 8 * (B_EMPTY2 + 1));
    bar_sync<128>(NB_WG2);
    reg_fence(o[0]); reg_fence(o[1]);
#pragma unroll
    for (int m = 0; m < 2; m++)
#pragma unroll
      for (int g = 0; g < 6; g++) {
        const float* d = &o[m][8 * g];
        stsm4(o_st + m * PUNIT + g * 256, pack_bf16(d[0], d[1]), pack_bf16(d[2], d[3]), pack_bf16(d[4], d[5]), pack_bf16(d[6], d[7]));
      }
    fence_async_smem();
    bar_sync<128>(NB_WG2);
    if (t == 0) { mbar_arrive(bars + 8 * B_QF); PROF(70); }
  }
#pragma unroll
  for (int i = 0; i < NP; i++) bar_arrive<256>(NB_PE + i);
  const uint32_t g_end = 8 * n_items;
  uint32_t g = 0;
  auto release = [&](uint32_t gg) {
    if (gg + NP < g_end) bar_arrive<256>(NB_PE + (gg & 3));
    if (lane == 0) mbar_arrive(bars + 8 * (B_EMPTY + 4 + (gg & 3)));
  };
  auto issue_pv = [&](auto first) {
    bar_sync<256>(NB_PF + (g & 3));
    wg_fence();
    const uint32_t da = vdesc + (g & 3) * (UNIT >> 4);
    const uint32_t db = pdesc + (g & 3) * (PUNIT >> 4);
#pragma unroll
    for (int kk = 0; kk < 4; kk++)
#pragma unroll
      for (int m = 0; m < 2; m++) {
        if (decltype(first)::value && kk == 0) wgmma96_first<1, 1>(o[m], da + ((m * 8192) >> 4), db, hi);
        else wgmma96<1, 1>(o[m], da + ((m * 8192 + kk * 2048) >> 4), db + ((kk * KSTEP) >> 4), 1, hi);
      }
    wg_commit();
    g++;
  };
  for (int n = 0; n < n_items; n++) {
    mbar_wait_w(bars + 8 * (B_FULL + 4), 0);
    issue_pv(BoolC<true>{});
#pragma unroll 1
    do {
      const uint32_t vb = bars + 8 * (B_FULL + 4 + (g & 3));
      bool held = true;
      if (__builtin_expect(!__all_sync(0xffffffffu, mbar_test(vb, (g >> 2) & 1)), 0)) {
        wg_wait<0>(); release(g - 1); held = false;
        ACC(0);
        mbar_wait_slow_w(vb, (g >> 2) & 1);
        ACC(1);
      }
      issue_pv(BoolC<false>{});
      wg_wait<1>();
      if (held) release(g - 2);
    } while (g & 7);
    ACC(0);
    bool bad = false;
    bar_sync<256>(NB_L);
    if (warp < 3) {
      float sum = 0.f;
#pragma unroll
      for (int i = 0; i < 4; i++) sum += __uint_as_float(lds32(sb + ATT_LP + i * 384 + 4 * t));
      bad = !(sum < SM_LIMIT);
      float inv; asm("rcp.approx.ftz.f32 %0, %1;" : "=f"(inv) : "f"(sum));
      sts32(sb + ATT_LINV + 4 * t, bad ? 0u : __float_as_uint(inv));
    }
    wg_wait<0>();
    reg_fence(o[0]); reg_fence(o[1]);
    release(g - 1);
    bad = __any_sync(0xffffffffu, bar_or128(NB_WG2R, bad));
    unsigned char* qsave = g_qsave + (size_t)blockIdx.x * IMG;
    if (__builtin_expect(bad, 0)) {
#pragma unroll 1
      for (int i = t; i < IMG / 4; i += 128) reinterpret_cast<uint32_t*>(qsave)[i] = lds32(sb + ATT_Q + (n & 1) * IMG + 4 * i);
      __threadfence();
      bar_sync<128>(NB_WG2);
    }
    const uint32_t dst = o_st + (n & 1) * IMG;
    uint32_t pk[48];
#pragma unroll
    for (int j = 0; j < 12; j++) {
      const float2 q = lds64f(sb + ATT_LINV + col_off + 32 * j);
#pragma unroll
      for (int m = 0; m < 2; m++) {
        pk[24 * m + 2 * j] = pack_bf16(o[m][4 * j] * q.x, o[m][4 * j + 1] * q.y);
        pk[24 * m + 2 * j + 1] = pack_bf16(o[m][4 * j + 2] * q.x, o[m][4 * j + 3] * q.y);
      }
    }
#pragma unroll
    for (int m = 0; m < 2; m++)
#pragma unroll
      for (int gq = 0; gq < 6; gq++)
        stsm4(dst + m * PUNIT + gq * 256, pk[24 * m + 4 * gq], pk[24 * m + 4 * gq + 1], pk[24 * m + 4 * gq + 2], pk[24 * m + 4 * gq + 3]);
    if (__builtin_expect(bad, 0)) {
      const int item = a + n * p.n_att;
      const size_t kvoff = (size_t)((item & 15) * NH + (item >> 4)) * SK * DH;
#pragma unroll 1
      for (int q = 0; q < SQ; q++)
        if (__all_sync(0xffffffffu, lds32(sb + ATT_LINV + 4 * q) == 0u))
          att_fallback(p.kp[c.br] + kvoff, p.vp[c.br] + kvoff, qsave, sb, sb + ATT_Q + (n & 1) * IMG, q, t);
    }
    fence_async_smem();
    bar_arrive<160>(NB_IO);
    ACC(6);
    if (t == 0 && n < 32) PROF(2 + n);
  }
  ACC_OUT(t == 0, 32);
}

constexpr int GQ_PF = 10;
constexpr int GO_PF = 8;

__device__ __forceinline__ void gq_producer(const Params& p, const Ctx& c) {
  const uint64_t polw = policy_w(), polx = policy_evict_normal();
  const uint32_t sb = c.sb, bars = sb + MISC_BAR;
  const int sub = c.idx & 1, pair = c.idx >> 1, b = pair * 2 + c.rank;
  const int col0 = (p.n_local / NB + sub) * DH + c.rank * 64, n_chunks = (NH - p.n_local / NB) / 2 * 10;
  int col = col0, kc = 0, pcol = col0, pkc = 4;
  auto prefetch = [&](int i) {
    if (i < n_chunks && (i & 7) == pair && elect_one()) tma2d_prefetch(&p.wq[c.br], pcol, pkc * 64, polw);
    if (++pkc == 10) { pkc = 0; pcol += 2 * DH; }
  };
#pragma unroll 1
  for (int i = 0; i < n_chunks; i++) {
    const uint32_t st = i & 3;
    mbar_wait_slow_w(bars + 8 * (B_GQE + st), ((i >> 2) & 1) ^ 1);
    if (elect_one()) {
      const bool lx = true;
      mbar_expect_tx(bars + 8 * (B_GQF + st), lx ? GQ_STAGE : 16384);
      tma2d_mc(sb + G_Q + st * GQ_STAGE + c.rank * 8192, &p.wq[c.br], col, kc * 64, bars + 8 * (B_GQF + st), polw);
      if (lx) tma2d(sb + G_Q + st * GQ_STAGE + 16384, &p.x[c.br], kc * 64, b * SQ, bars + 8 * (B_GQF + st), polx);
    }
    if (++kc == 10) { kc = 0; col += 2 * DH; }
    if (i == 3) { for (int j = 4; j < 4 + GQ_PF; j++) prefetch(j); }
    else if (i > 3) prefetch(i + GQ_PF);
  }
}

__device__ __forceinline__ void gq_flags(const Params& p, const Ctx& c) {
  const int sub = c.idx & 1, b = (c.idx >> 1) * 2 + c.rank;
  for (int h = p.n_local / NB + sub; h < NH; h += 2) {
    if (h >= RING_H) {
      flag_wait(&g_odone[((c.br * NB + b) * 2 + 0) * FLAG_STRIDE], c.seq0 + h - RING_H);
      flag_wait(&g_odone[((c.br * NB + b) * 2 + 1) * FLAG_STRIDE], c.seq0 + h - RING_H);
    }
    bar_arrive<160>(NB_GSLOT);
    bar_sync<160>(NB_GDONE);
    const int tile = tile_id(c.br, h, b);
    if (elect_one()) st_release(&g_qflag[tile * FLAG_STRIDE], ((c.seq0 + h) << 1) | tile_pol(c, tile));
    __syncwarp();
  }
}

__device__ __forceinline__ void gq_consumer(const Params& p, const Ctx& c) {
  const DescHi hi{p.hi_sw, p.hi_sw2, p.hi_img};
  const Tid T; const int warp = T.warp, lane = T.lane;
  const uint32_t sb = c.sb, bars = sb + MISC_BAR;
  const int sub = c.idx & 1, b = (c.idx >> 1) * 2 + c.rank;
  const uint32_t desc0 = desc_sw128(sb + G_Q);
  float d[2][48];
  ACC_DECL
  uint32_t i = 0;
  auto release = [&](uint32_t j) { if (lane < 2) mbar_arrive_cluster(bars + 8 * (B_GQE + (j & 3)), lane); };
  auto issue = [&](auto first) {
    wg_fence();
    const uint32_t da = desc0 + (i & 3) * (GQ_STAGE >> 4), db = da + (16384 >> 4);
#pragma unroll
    for (int kk = 0; kk < 4; kk++)
#pragma unroll
      for (int m = 0; m < 2; m++) {
        if (decltype(first)::value && kk == 0) wgmma96_first<1, 0>(d[m], da + ((m * 8192) >> 4), db, hi);
        else wgmma96<1, 0>(d[m], da + ((m * 8192 + kk * 2048) >> 4), db + ((kk * 32) >> 4), 1, hi);
      }
    wg_commit();
    i++;
  };
  for (int h = p.n_local / NB + sub; h < NH; h += 2) {
    mbar_wait_w(bars + 8 * (B_GQF + (i & 3)), (i >> 2) & 1);
    issue(BoolC<true>{});
#pragma unroll 1
    for (int kc = 1; kc < 10; kc++) {
      const uint32_t fb = bars + 8 * (B_GQF + (i & 3));
      bool held = true;
      if (!__all_sync(0xffffffffu, mbar_test(fb, (i >> 2) & 1))) {
        wg_wait<0>(); release(i - 1); held = false;
        ACC(0);
        mbar_wait_slow_w(fb, (i >> 2) & 1);
        ACC(1);
      }
      issue(BoolC<false>{});
      wg_wait<1>();
      if (held) release(i - 2);
    }
    wg_wait<0>();
    reg_fence(d[0]); reg_fence(d[1]);
    release(i - 1);
    const int tile = tile_id(c.br, h, b);
    const uint32_t pl = tile_pol(c, tile);
    ACC(0);
    bar_sync<160>(NB_GSLOT);
    store_image(tile_step(tile, warp, pl) + lane * 4, d[0]);
    store_image(tile_step(tile, 4 + warp, pl) + lane * 4, d[1]);
    bar_arrive<160>(NB_GDONE);
    if (T.t == 0) PROF(100 + (h >> 1));
    ACC(2);
  }
  ACC_OUT(T.t == 0, 64);
}

__device__ __forceinline__ void go_wproducer(const Params& p, const Ctx& c) {
  const uint64_t pol = policy_w();
  const uint32_t sb = c.sb, bars = sb + MISC_BAR;
  const int sub = c.idx & 1, pair = c.idx >> 1;
  auto prefetch = [&](int j) {
    if (j < 128 && (j & 7) == pair && elect_one()) tma3d_prefetch(&p.wo[c.br], 0, j * 32 + c.rank * 16, sub * 5, pol);
  };
#pragma unroll 1
  for (int i = 0; i < 128; i++) {
    const uint32_t st = i & 3;
    mbar_wait_slow_w(bars + 8 * (B_GOE + st), ((i >> 2) & 1) ^ 1);
    if (elect_one()) {
      mbar_expect_tx(bars + 8 * (B_GOF + st), 20480);
      tma3d_mc(sb + G_O + st * GO_STAGE + c.rank * 10240, &p.wo[c.br], 0, i * 32 + c.rank * 16, sub * 5, bars + 8 * (B_GOF + st), pol);
    }
    if (i == 4) { for (int j = 5; j <= 4 + GO_PF; j++) prefetch(j); }
    else if (i > 4) prefetch(i + GO_PF);
  }
}

__device__ __forceinline__ void go_oproducer(const Ctx& c) {
  const uint32_t sb = c.sb, bars = sb + MISC_BAR;
  const int lane = threadIdx.x & 31;
  const int sub = c.idx & 1, b = (c.idx >> 1) * 2 + c.rank;
  int ready = 0;
  uint32_t pols = 0;
  for (int h = 0; h < NH; h++) {
    if (h >= ready) {
      uint32_t it = 0;
#pragma unroll 1
      while (true) {
        uint32_t v = 0; bool ok = false;
        if (lane < 4 && h + lane < NH) {
          v = ld_acquire(&g_oflag[tile_id(c.br, h + lane, b) * FLAG_STRIDE]);
          ok = (int32_t)(v - ((c.seq0 + h + lane) << 1)) >= 0;
        }
        const int cnt = __ffs(~__ballot_sync(0xffffffffu, ok)) - 1;
        pols = __ballot_sync(0xffffffffu, v & 1);
        if (cnt > 0) { ready = h + cnt; break; }
        if (++it > (1u << 22)) { die(); break; }
        __nanosleep(20);
      }
      __syncwarp();
      fence_async_global();
    }
    const int tile = tile_id(c.br, h, b);
    if (lane == 0) PROF(130 + h);
#pragma unroll 1
    for (int st = 0; st < 4; st++) {
      mbar_wait_slow_w(bars + 8 * (B_GOE + st), (h & 1) ^ 1);
      if (lane == 0) mbar_expect_tx(bars + 8 * (B_GOF + st), 2 * KSTEP);
      __syncwarp();
      if (lane < 2) bulk_load(sb + G_O + st * GO_STAGE + 20480 + lane * KSTEP, tile_step(tile, 2 * st + lane, pols & 1), KSTEP, bars + 8 * (B_GOF + st));
    }
    if (lane == 0) PROF(170 + h);
    pols >>= 1;
    if (h >= 1 && lane == 0) st_relaxed(&g_odone[((c.br * NB + b) * 2 + sub) * FLAG_STRIDE], (c.seq0 + h - 1) << 1);
    __syncwarp();
  }
}

template <int NT>
__device__ __forceinline__ void go_consumer(const Params& p, const Ctx& c) {
  const DescHi hi{p.hi_sw, p.hi_sw2, p.hi_img};
  const Tid T; const int warp = T.warp, lane = T.lane;
  const uint32_t sb = c.sb, bars = sb + MISC_BAR;
  const int sub = c.idx & 1, b = (c.idx >> 1) * 2 + c.rank;
  constexpr int t0 = NT == 3 ? 0 : 3;
  const uint32_t adesc = desc_sw128(sb + G_O + t0 * 2048), bdesc = desc_img(sb + G_O + 20480);
  float d[NT][48];
  uint32_t i = 0;
  auto release = [&](uint32_t j) { if (lane < 2) mbar_arrive_cluster(bars + 8 * (B_GOE + (j & 3)), lane); };
  auto issue = [&](auto first) {
    wg_fence();
    const uint32_t off = (i & 3) * (GO_STAGE >> 4);
#pragma unroll
    for (int kk = 0; kk < 2; kk++)
#pragma unroll
      for (int t = 0; t < NT; t++) {
        if (decltype(first)::value && kk == 0) wgmma96_first<1, 1>(d[t], adesc + off + ((t * 2048) >> 4), bdesc + off, hi);
        else wgmma96<1, 1>(d[t], adesc + off + ((kk * 10240 + t * 2048) >> 4), bdesc + off + ((kk * KSTEP) >> 4), 1, hi);
      }
    wg_commit();
    i++;
  };
  mbar_wait_slow_w(bars + 8 * B_GOF, 0);
  issue(BoolC<true>{});
#pragma unroll 1
  do {
    const uint32_t fb = bars + 8 * (B_GOF + (i & 3));
    bool held = true;
    if (!__all_sync(0xffffffffu, mbar_test(fb, (i >> 2) & 1))) {
      wg_wait<0>(); release(i - 1); held = false;
      mbar_wait_slow_w(fb, (i >> 2) & 1);
    }
    issue(BoolC<false>{});
    wg_wait<1>();
    if (held) release(i - 2);
    if (T.tid == 0 && (i & 3) == 0) PROF(2 + (i >> 2) - 1);
  } while (i < 128);
  wg_wait<0>();
#pragma unroll
  for (int t = 0; t < NT; t++) reg_fence(d[t]);
  const uint32_t stg = sb + G_Q + t0 * 12288;
  const uint32_t st_addr = stg + ((lane >> 4) * 8 + (lane & 7)) * 128 + (((warp * 2 + ((lane >> 3) & 1)) ^ (lane & 7)) << 4);
#pragma unroll
  for (int t = 0; t < NT; t++)
#pragma unroll
    for (int g = 0; g < 6; g++) {
      const float* e = &d[t][8 * g];
      stsm4_t(st_addr + t * 12288 + g * 2048, pack_bf16(e[0], e[1]), pack_bf16(e[2], e[3]), pack_bf16(e[4], e[5]), pack_bf16(e[6], e[7]));
    }
  fence_async_smem();
  bar_sync<128>(NB_GWG + (NT == 3 ? 0 : 1));
  if (T.t == 0) {
#pragma unroll
    for (int t = 0; t < NT; t++) tma2d_store(&p.out, c.br * DM + sub * 320 + (t0 + t) * 64, b * SQ, stg + t * 12288);
    bulk_commit();
    bulk_wait_read();
  }
}

__device__ __forceinline__ uint32_t timed_atomic(uint32_t* p) {
  uint32_t t0, t1, v;
  asm volatile("mov.u32 %0, %%clock; atom.global.exch.b32 %1, [%2], %0;" : "=&r"(t0), "=r"(v) : "l"(p) : "memory");
  asm volatile("{.reg .pred q; setp.ne.u32 q, %1, %2; mov.u32 %0, 0; @q mov.u32 %0, %%clock;}" : "=r"(t1) : "r"(v), "r"(t0) : "memory");
  return t1 - t0;
}

__global__ void __cluster_dims__(2, 1, 1) __launch_bounds__(NTHREADS, 1)
fused_attn_kernel(const __grid_constant__ Params p) {
  extern __shared__ __align__(1024) unsigned char smem[];
  const uint32_t sb = smem_u32(smem);
  const int tid = threadIdx.x, wi = __shfl_sync(0xffffffffu, tid >> 5, 0), lane = tid & 31;
  const int cid = blockIdx.x >> 1, rank = blockIdx.x & 1;
  const uint32_t bars = sb + MISC_BAR;

  uint32_t epoch = 0;
  if (wi == 0) {
    epoch = *reinterpret_cast<volatile uint32_t*>(&g_epoch[blockIdx.x * FLAG_STRIDE]);
  }
  if (wi == 14 && lane < 11) asm volatile("prefetch.tensormap [%0];" ::"l"(&p.x[0] + lane) : "memory");
  if (tid == NTHREADS - 32) {
    PROF(0);
    for (int i = 0; i < 8; i++) {
      mbar_init(bars + 8 * (B_FULL + i), 1); mbar_init(bars + 8 * (B_EMPTY + i), 4);
      mbar_init(bars + 8 * (B_FULL2 + i), 1); mbar_init(bars + 8 * (B_EMPTY2 + i), 4);
    }
    for (int i = 0; i < 2; i++) mbar_init(bars + 8 * (B_QF + i), 1);
    for (int i = 0; i < 4; i++) {
      mbar_init(bars + 8 * (B_GQF + i), 1); mbar_init(bars + 8 * (B_GQE + i), 8);
      mbar_init(bars + 8 * (B_GOF + i), 2); mbar_init(bars + 8 * (B_GOE + i), 16);
    }
    asm volatile("fence.mbarrier_init.release.cluster;" ::: "memory");
  }
  __syncwarp();
  const uint32_t poff = blockIdx.x * 8192 + KSTEP;
#pragma unroll 1
  for (int pg = wi >> 1; pg < N_PAGES; pg += 8) {
    uint32_t* pa = reinterpret_cast<uint32_t*>(scratch_base() + ((size_t)pg << 21) + poff + (wi & 1) * 4096);
    if (lane < 8) pa[lane] = 0;
    __syncwarp();
    if (lane == 0) {
      uint32_t tm = 0xffffffffu;
#pragma unroll 1
      for (int r = 0; r < PROBE_N; r++) tm = min(tm, timed_atomic(pa));
      sts32(sb + MISC + 8 * pg + 4 * (wi & 1), tm);
    }
    __syncwarp();
    if (pg == 0 && wi == 1) bar_arrive<64>(1);
  }
  if (EARLY_PF && wi == 2 && lane < 4) {
    const int j = blockIdx.x * 4 + lane, br = j & 1, r = j >> 1;
    if (r < 160) tma2d_prefetch(&p.x[br], (r % 10) * 64, (r / 10) * SQ, policy_evict_normal());
    else if (r < 240) tma2d_prefetch(&p.wq[br], ((r - 160) & 7) * 64, ((r - 160) >> 3) * 64, policy_w());
  }
  if (wi == 0) {
    if (lane == 0) PROF(240);
    bar_sync<64>(1);
    if (lane == 0 && epoch != 0xffffffffu) PROF(241);
    const uint32_t tag = (epoch + 1) << 1;
    if (lane == 0) {
      const uint32_t side = chunk_par(poff) ^ (lds32(sb + MISC + 4) < lds32(sb + MISC));
      if (rank == 0) st_relaxed(&g_side[cid], tag | ((AWARE & 1) ? side : (uint32_t)((cid >> 3) & 1)));
      g_epoch[blockIdx.x * FLAG_STRIDE] = epoch + 1;
    }
    uint32_t v[3], it = 0;
    while (true) {
      bool ok = true;
#pragma unroll
      for (int j = 0; j < 3; j++) {
        v[j] = tag;
        if (lane + 32 * j < p.n_clusters) asm volatile("ld.relaxed.gpu.global.u32 %0, [%1];" : "=r"(v[j]) : "l"(&g_side[lane + 32 * j]) : "memory");
        ok &= (v[j] | 1) == (tag | 1);
      }
      if (__all_sync(0xffffffffu, ok)) break;
      if (++it > (1u << 22)) { die(); break; }
    }
    if (lane == 0) PROF(242);
    int ones = 0, ones_below = 0, mine = 0;
#pragma unroll
    for (int j = 0; j < 3; j++) {
      const uint32_t m = __ballot_sync(0xffffffffu, v[j] & 1);
      ones += __popc(m);
      if (cid >= 32 * (j + 1)) ones_below += __popc(m);
      else if (cid >= 32 * j) { ones_below += __popc(m & ((1u << (cid - 32 * j)) - 1)); mine = (m >> (cid - 32 * j)) & 1; }
    }
    const int pos = mine ? p.n_clusters - ones + ones_below : cid - ones_below;
    if (lane == 0) { sts32(sb + MISC + 128, pos); sts32(sb + MISC + 132, epoch); }
  }
  __syncthreads();
  if (tid == 0) PROF(243);
  asm volatile("barrier.cluster.arrive.relaxed.aligned;" ::: "memory");
  Ctx c;
  c.sb = sb; c.rank = rank;
  const int pos = __shfl_sync(0xffffffffu, lds32(sb + MISC + 128), 0);
  c.seq0 = __shfl_sync(0xffffffffu, lds32(sb + MISC + 132), 0) * NH + 1;
  c.pol = __ballot_sync(0xffffffffu, lane < N_PAGES && (chunk_par(poff) ^ (lds32(sb + MISC + 8 * (lane & 15) + 4) < lds32(sb + MISC + 8 * (lane & 15)))));
  c.br = pos >= p.half;
  const int k = pos - c.br * p.half;
  int role = p.role[k];
  c.idx = p.idx[k];
  asm volatile("barrier.cluster.wait.aligned;" ::: "memory");
  if (tid == 0) { PROF(254); PROFV(250, 16 * (role * 1000 + c.br * 100 + c.idx + 1)); PROFV(251, 16 * (c.pol + 65536)); }

  const int a = c.idx * 2 + rank;
  const int n_items = p.items_base + (a < p.items_extra);
  if (wi >= 12) {
    asm volatile("setmaxnreg.dec.sync.aligned.u32 32;");
    const int pw = wi - 12;
    if (role == ROLE_ATT) {
      if (pw == 1) att_qloader(p, c, a, n_items);
      else if (pw == 2) att_storer(p, c, a, n_items);
      else att_producer(p, c, a, n_items, pw == 3);
    } else if (role == ROLE_G) {
      if (pw == 0) gq_producer(p, c);
      else if (pw == 1) go_oproducer(c);
      else if (pw == 2) gq_flags(p, c);
      else go_wproducer(p, c);
    }
    asm volatile("barrier.cluster.arrive.relaxed.aligned; barrier.cluster.wait.aligned; // producer" ::: "memory");
  } else if (wi >= 8) {
    if (role == ROLE_ATT) att_pv_wg(p, c, a, n_items);
    else if (role == ROLE_G) gq_consumer(p, c);
    asm volatile("barrier.cluster.arrive.relaxed.aligned; barrier.cluster.wait.aligned; // wg2" ::: "memory");
  } else {
    asm volatile("setmaxnreg.inc.sync.aligned.u32 176;");
    if (role == ROLE_ATT) att_softmax_wg(p, sb, n_items);
    else if (role == ROLE_G) { if (wi < 4) go_consumer<3>(p, c); else go_consumer<2>(p, c); }
    if (tid == 0) PROF(255);
    asm volatile("barrier.cluster.arrive.relaxed.aligned; barrier.cluster.wait.aligned; // consumer" ::: "memory");
  }
}

typedef CUresult (*EncodeFn)(CUtensorMap*, CUtensorMapDataType, cuuint32_t, void*, const cuuint64_t*, const cuuint64_t*,
                             const cuuint32_t*, const cuuint32_t*, CUtensorMapInterleave, CUtensorMapSwizzle,
                             CUtensorMapL2promotion, CUtensorMapFloatOOBfill);

void encode(EncodeFn enc, CUtensorMap* m, void* ptr, int rank, const cuuint64_t* dims, const cuuint64_t* strides, const cuuint32_t* box) {
  cuuint32_t es[3] = {1, 1, 1};
  enc(m, CU_TENSOR_MAP_DATA_TYPE_BFLOAT16, rank, ptr, dims, strides, box, es, CU_TENSOR_MAP_INTERLEAVE_NONE,
      CU_TENSOR_MAP_SWIZZLE_128B, CU_TENSOR_MAP_L2_PROMOTION_L2_128B, CU_TENSOR_MAP_FLOAT_OOB_FILL_NONE);
}

}

extern "C" void kernel_launch(void* const* d_in, const int* in_sizes, int n_in, void* d_out, int out_size) {
  (void)in_sizes; (void)n_in; (void)out_size;
  static EncodeFn enc = nullptr;
  static int n_clusters = 0;
  if (!enc) {
    cudaDriverEntryPointQueryResult qr;
    cudaGetDriverEntryPoint("cuTensorMapEncodeTiled", (void**)&enc, cudaEnableDefault, &qr);
    cudaFuncSetAttribute(fused_attn_kernel, cudaFuncAttributeMaxDynamicSharedMemorySize, SMEM_BYTES);
    cudaLaunchConfig_t cfg = {};
    cfg.gridDim = dim3(128); cfg.blockDim = dim3(NTHREADS); cfg.dynamicSmemBytes = SMEM_BYTES;
    cudaLaunchAttribute at[1];
    at[0].id = cudaLaunchAttributeClusterDimension; at[0].val.clusterDim.x = 2; at[0].val.clusterDim.y = 1; at[0].val.clusterDim.z = 1;
    cfg.attrs = at; cfg.numAttrs = 1;
    int mx = 0;
    cudaOccupancyMaxActiveClusters(&mx, fused_attn_kernel, &cfg);
    n_clusters = mx < 66 ? mx : 66;
    if (n_clusters < 34) n_clusters = 34;
  }
  Params p;
  for (int br = 0; br < 2; br++) {
    void* x = d_in[5 * br + 0]; void* k = d_in[5 * br + 1]; void* v = d_in[5 * br + 2];
    void* wq = d_in[5 * br + 3]; void* wo = d_in[5 * br + 4];
    p.kp[br] = (const __nv_bfloat16*)k; p.vp[br] = (const __nv_bfloat16*)v;
    { cuuint64_t d[2] = {DM, NB * SQ}, s[1] = {DM * 2}; cuuint32_t bx[2] = {64, SQ}; encode(enc, &p.x[br], x, 2, d, s, bx); }
    { cuuint64_t d[2] = {NH * DH, DM}, s[1] = {NH * DH * 2}; cuuint32_t bx[2] = {64, 64}; encode(enc, &p.wq[br], wq, 2, d, s, bx); }
    { cuuint64_t d[3] = {64, NB * NH * SK, 2}, s[2] = {DH * 2, 128}; cuuint32_t bx[3] = {64, 64, 2};
      encode(enc, &p.k[br], k, 3, d, s, bx); encode(enc, &p.v[br], v, 3, d, s, bx); }
    { cuuint64_t d[3] = {64, NH * DH, 10}, s[2] = {DM * 2, 128}; cuuint32_t bx[3] = {64, 16, 5}; encode(enc, &p.wo[br], wo, 3, d, s, bx); }
  }
  { cuuint64_t d[2] = {2 * DM, NB * SQ}, s[1] = {2 * DM * 2}; cuuint32_t bx[2] = {64, SQ}; encode(enc, &p.out, d_out, 2, d, s, bx); }
  p.hi_sw = p.hi_sw2 = SW128_HI; p.hi_img = IMG_HI;
  p.n_clusters = n_clusters; p.half = n_clusters / 2;
  const int att_cl = p.half - 16 < ATT_CL ? p.half - 16 : ATT_CL;
  p.n_att = 2 * att_cl;
  p.items_base = NB * NH / p.n_att; p.items_extra = NB * NH % p.n_att;
  p.n_local = p.n_att >= 2 * NB ? 2 * NB : 0;
  int cnt[2] = {0, 0};
  const int lim[2] = {att_cl, 16};
  for (int k = 0; k < 40; k++) {
    int role = (k >> 2) & 1;
    if (cnt[role] >= lim[role]) role ^= 1;
    if (cnt[role] >= lim[role] || k >= p.half) role = ROLE_NONE;
    p.role[k] = (unsigned char)role; p.idx[k] = role == ROLE_NONE ? 0 : (unsigned char)cnt[role]++;
  }
  fused_attn_kernel<<<2 * n_clusters, NTHREADS, SMEM_BYTES, cudaStreamPerThread>>>(p);
}
```

```cpp
#include <cuda_runtime.h>
#include <cuda_bf16.h>
#include <cuda.h>
#include <stdint.h>

namespace {

constexpr int ATT_CL = 17;
constexpr int RING_H = 8;
constexpr int S_SPLIT = 4;
constexpr int PROBE_N = 2;
constexpr int AHEAD = 2, AHEAD_T = 3;
constexpr int AHEAD_H = 4, FREE = 16;
constexpr int ENDN = 32, AHEAD_E = 4;
constexpr int GRADE = 6;
constexpr int ST_KV = 6, ST_BURST = 2, ST_DT1 = 150, ST_DT2 = 400;
constexpr int WQ_G0 = 12, WQ_G = 4, WQ_M = 6;
constexpr int WO_N = 10, WO_T0 = 300, WO_DT = 200;

constexpr int NB = 16, SQ = 96, DM = 640, NH = 32, SK = 512, DH = 128;
constexpr int IMG = 24576;
constexpr int KSTEP = 3072;
constexpr int NTHREADS = 512;
constexpr int TILE_SPAN = 65536;
constexpr int N_PAGES = (RING_H * NB * TILE_SPAN + (1 << 21) - 1) / (1 << 21);
static_assert(N_PAGES <= 8, "");

constexpr int UNIT = 16384;
constexpr int PUNIT = 4 * KSTEP;
constexpr int NP = 4;
constexpr int ATT_K = 0;
constexpr int ATT_V = 4 * UNIT;
constexpr int ATT_Q = 8 * UNIT;
constexpr int ATT_P = ATT_Q + 2 * IMG;
constexpr int ATT_MX = ATT_P + NP * PUNIT;
constexpr int ATT_LINV = ATT_MX + 384;
constexpr int ATT_LP = ATT_LINV + 384;
constexpr int GQ_STAGE = 16384 + 12288;
constexpr int GO_STAGE = 20480 + 2 * KSTEP;
constexpr int GQ_N = 4, GO_N = 3;
constexpr int GO_N2 = 8, GO_SWITCH = 108;
constexpr int G_O = 0;
constexpr int G_Q = GO_N * GO_STAGE;
constexpr int G_XS = G_Q + GQ_N * 16384;
constexpr int G_XR = G_XS + 2 * 12288;
static_assert(GO_SWITCH % (2 * GO_N) == 0 && (124 - GO_SWITCH) % GO_N2 == 0 && G_Q % 1024 == 0, "");
constexpr int MISC = 231744;
constexpr int MISC_BAR = 231936;
constexpr int SMEM_BYTES = MISC_BAR + 512;
static_assert(ATT_LP + 1536 <= MISC, "");
static_assert(G_XR + 5 * 12288 <= MISC && 2 * GQ_STAGE <= G_Q && GO_N2 * GO_STAGE <= MISC, "");

constexpr int B_FULL = 0;
constexpr int B_EMPTY = 8;
constexpr int B_QF = 16;
constexpr int B_SEAT = 18;
constexpr int B_ODONE = 44;
constexpr int B_FULL2 = 48;
constexpr int B_EMPTY2 = 56;
constexpr int B_GQF = 0;
constexpr int B_GQE = 20;
constexpr int B_GXF = 5;
constexpr int B_GXE = 25;
constexpr int B_QPH = 26;
constexpr int B_GOF = 28;
constexpr int B_GOE = 36;
constexpr int NB_QE = 0, NB_WG0 = 1, NB_MX = 2, NB_L = 3, NB_WG2 = 4, NB_WG2R = 5, NB_L0 = 6, NB_PF = 8  , NB_PE = 12  ;
constexpr int NB_GSLOT = 1, NB_GDONE = 2, NB_GEPI = 3, NB_GWG = 4  ;

enum { ROLE_ATT = 0, ROLE_G = 1, ROLE_NONE = 2 };

struct Params {
  CUtensorMap x[2], wq[2], k[2], v[2], wo[2], out;
  CUtensorMap tile[2], quarter[2];
  const __nv_bfloat16* kp[2]; const __nv_bfloat16* vp[2];
  const unsigned char* wqp[2]; const unsigned char* wop[2];
  int n_clusters, half;
  int n_att, n_local, items_base, items_extra;
  uint32_t hi_sw, hi_sw2, hi_img;
  unsigned char role[40], idx[40];
};

__device__ unsigned char g_scratch_raw[(size_t)(N_PAGES + 1) << 21];
__device__ unsigned long long g_ticket;
__device__ uint32_t g_rel;
__device__ uint32_t g_prog[2 * 2 * 32];

__device__ __forceinline__ long long globaltimer_ns() { long long t; asm volatile("mov.u64 %0, %%globaltimer;" : "=l"(t)); return t; }
__device__ __forceinline__ bool elect_one() {
  uint32_t r;
  asm volatile("{.reg .pred p; elect.sync _|p, 0xffffffff; selp.u32 %0, 1, 0, p;}" : "=r"(r));
  return r;
}
__device__ __forceinline__ uint32_t smem_u32(const void* p) { return (uint32_t)__cvta_generic_to_shared(p); }
__device__ __forceinline__ void mbar_init(uint32_t bar, uint32_t cnt) {
  asm volatile("mbarrier.init.shared::cta.b64 [%0], %1;" ::"r"(bar), "r"(cnt) : "memory");
}
__device__ __forceinline__ void mbar_expect_tx(uint32_t bar, uint32_t bytes) {
  asm volatile("mbarrier.arrive.expect_tx.shared::cta.b64 _, [%0], %1;" ::"r"(bar), "r"(bytes) : "memory");
}
__device__ __forceinline__ void mbar_arrive(uint32_t bar) {
  asm volatile("mbarrier.arrive.shared::cta.b64 _, [%0];" ::"r"(bar) : "memory");
}
__device__ __forceinline__ void mbar_arrive_cluster(uint32_t bar, uint32_t cta) {
  asm volatile("{.reg .b32 ra; mapa.shared::cluster.u32 ra, %0, %1; mbarrier.arrive.shared::cluster.b64 _, [ra];}"
               ::"r"(bar), "r"(cta) : "memory");
}
__device__ __forceinline__ bool mbar_try(uint32_t bar, uint32_t parity) {
  uint32_t ok;
  asm volatile("{.reg .pred p; mbarrier.try_wait.parity.shared::cta.b64 p, [%1], %2; selp.u32 %0, 1, 0, p;}"
               : "=r"(ok) : "r"(bar), "r"(parity) : "memory");
  return ok;
}
__device__ __forceinline__ bool mbar_test(uint32_t bar, uint32_t parity) {
  uint32_t ok;
  asm volatile("{.reg .pred p; mbarrier.test_wait.parity.shared::cta.b64 p, [%1], %2; selp.u32 %0, 1, 0, p;}"
               : "=r"(ok) : "r"(bar), "r"(parity) : "memory");
  return ok;
}
__device__ __forceinline__ void die() { asm volatile("st.global.u32 [%0], %1;" ::"l"(0ull), "r"(0u) : "memory"); }
__device__ __forceinline__ bool mbar_try_long(uint32_t bar, uint32_t parity) {
  uint32_t ok;
  asm volatile("{.reg .pred p; mbarrier.try_wait.parity.shared::cta.b64 p, [%1], %2, %3; selp.u32 %0, 1, 0, p;}"
               : "=r"(ok) : "r"(bar), "r"(parity), "r"(2000u) : "memory");
  return ok;
}
__device__ __forceinline__ void mbar_wait_slow_w(uint32_t bar, uint32_t parity) {
  uint32_t it = 0;
#pragma unroll 1
  while (!__all_sync(0xffffffffu, mbar_try_long(bar, parity))) { if (++it > (1u << 22)) { die(); break; } }
}
__device__ __forceinline__ void mbar_wait_w(uint32_t bar, uint32_t parity) {
  if (__builtin_expect(!__all_sync(0xffffffffu, mbar_try(bar, parity)), 0)) mbar_wait_slow_w(bar, parity);
}
__device__ __forceinline__ uint32_t ld_acquire(const uint32_t* p) {
  uint32_t v; asm volatile("ld.acquire.gpu.global.u32 %0, [%1];" : "=r"(v) : "l"(p) : "memory"); return v;
}
__device__ __forceinline__ void st_release(uint32_t* p, uint32_t v) {
  asm volatile("st.release.gpu.global.u32 [%0], %1;" ::"l"(p), "r"(v) : "memory");
}
__device__ __forceinline__ void flag_wait(const uint32_t* p, uint32_t seq) {
  uint32_t it = 0;
#pragma unroll 1
  while (!__all_sync(0xffffffffu, (int32_t)(ld_acquire(p) - seq) >= 0)) {
    if (++it > (1u << 22)) { die(); break; }
    __nanosleep(20);
  }
}
__device__ __forceinline__ void st_relaxed(uint32_t* p, uint32_t v) {
  asm volatile("st.relaxed.gpu.global.u32 [%0], %1;" ::"l"(p), "r"(v) : "memory");
}
__device__ __forceinline__ void fence_async_global() { asm volatile("fence.proxy.async.global;" ::: "memory"); }
__device__ __forceinline__ void fence_async_smem() { asm volatile("fence.proxy.async.shared::cta;" ::: "memory"); }

__device__ __forceinline__ void tma2d_store(const CUtensorMap* m, int c0, int c1, uint32_t src) {
  asm volatile("cp.async.bulk.tensor.2d.global.shared::cta.bulk_group [%0, {%1, %2}], [%3];"
               ::"l"(m), "r"(c0), "r"(c1), "r"(src) : "memory");
}
__device__ __forceinline__ void tma4d(uint32_t dst, const CUtensorMap* m, int c3, uint32_t bar) {
  asm volatile("cp.async.bulk.tensor.4d.shared::cluster.global.mbarrier::complete_tx::bytes [%0], [%1, {%3, %3, %3, %4}], [%2];"
               ::"r"(dst), "l"(m), "r"(bar), "r"(0), "r"(c3) : "memory");
}
__device__ __forceinline__ void bulk_commit() { asm volatile("cp.async.bulk.commit_group;" ::: "memory"); }
__device__ __forceinline__ void bulk_wait_read() { asm volatile("cp.async.bulk.wait_group.read 0;" ::: "memory"); }
__device__ __forceinline__ void tma2d(uint32_t dst, const CUtensorMap* m, int c0, int c1, uint32_t bar) {
  asm volatile("cp.async.bulk.tensor.2d.shared::cluster.global.mbarrier::complete_tx::bytes [%0], [%1, {%3, %4}], [%2];"
               ::"r"(dst), "l"(m), "r"(bar), "r"(c0), "r"(c1) : "memory");
}
__device__ __forceinline__ void tma2d_mc(uint32_t dst, const CUtensorMap* m, int c0, int c1, uint32_t bar) {
  asm volatile("cp.async.bulk.tensor.2d.shared::cluster.global.mbarrier::complete_tx::bytes.multicast::cluster [%0], [%1, {%3, %4}], [%2], %5;"
               ::"r"(dst), "l"(m), "r"(bar), "r"(c0), "r"(c1), "h"((uint16_t)3) : "memory");
}
__device__ __forceinline__ void tma3d(uint32_t dst, const CUtensorMap* m, int c0, int c1, int c2, uint32_t bar, uint64_t pol) {
  asm volatile("cp.async.bulk.tensor.3d.shared::cluster.global.mbarrier::complete_tx::bytes.L2::cache_hint [%0], [%1, {%3, %4, %5}], [%2], %6;"
               ::"r"(dst), "l"(m), "r"(bar), "r"(c0), "r"(c1), "r"(c2), "l"(pol) : "memory");
}
__device__ __forceinline__ void tma3d_mc(uint32_t dst, const CUtensorMap* m, int c0, int c1, int c2, uint32_t bar) {
  asm volatile("cp.async.bulk.tensor.3d.shared::cluster.global.mbarrier::complete_tx::bytes.multicast::cluster [%0], [%1, {%3, %4, %5}], [%2], %6;"
               ::"r"(dst), "l"(m), "r"(bar), "r"(c0), "r"(c1), "r"(c2), "h"((uint16_t)3) : "memory");
}
__device__ __forceinline__ void bulk_prefetch(const void* src, uint32_t bytes) {
  asm volatile("cp.async.bulk.prefetch.L2.global [%0], %1;" ::"l"(src), "r"(bytes) : "memory");
}
__device__ __forceinline__ void tma2d_prefetch(const CUtensorMap* m, int c0, int c1) {
  asm volatile("cp.async.bulk.prefetch.tensor.2d.L2.global [%0, {%1, %2}];" ::"l"(m), "r"(c0), "r"(c1) : "memory");
}
__device__ __forceinline__ void tma3d_prefetch_pol(const CUtensorMap* m, int c0, int c1, int c2, uint64_t pol) {
  asm volatile("cp.async.bulk.prefetch.tensor.3d.L2.global.L2::cache_hint [%0, {%1, %2, %3}], %4;"
               ::"l"(m), "r"(c0), "r"(c1), "r"(c2), "l"(pol) : "memory");
}
__device__ __forceinline__ uint64_t policy_evict_first() {
  uint64_t p; asm volatile("createpolicy.fractional.L2::evict_first.b64 %0, 1.0;" : "=l"(p)); return p;
}

__device__ __forceinline__ void wg_fence() { asm volatile("wgmma.fence.sync.aligned;" ::: "memory"); }
__device__ __forceinline__ void wg_commit() { asm volatile("wgmma.commit_group.sync.aligned;" ::: "memory"); }
template <int N> __device__ __forceinline__ void wg_wait() { asm volatile("wgmma.wait_group.sync.aligned %0;" ::"n"(N) : "memory"); }
__device__ __forceinline__ void reg_fence(float (&d)[48]) {
#pragma unroll
  for (int i = 0; i < 48; i++) asm volatile("" : "+f"(d[i])::"memory");
}

constexpr uint32_t SW128_HI = (1u << 30) | (1024 >> 4), SW128_LO = 1u << 16;
constexpr uint32_t IMG_HI = 128 >> 4, IMG_LO = (1536 >> 4) << 16;
__device__ __forceinline__ uint32_t desc_sw128(uint32_t addr) { return SW128_LO | ((addr & 0x3FFFF) >> 4); }
__device__ __forceinline__ uint32_t desc_img(uint32_t addr) { return IMG_LO | ((addr & 0x3FFFF) >> 4); }

struct DescHi { uint32_t sw, sw2, img; };
template <int TA, int TB>
__device__ __forceinline__ void wgmma96(float (&d)[48], uint32_t da, uint32_t db, int scale_d, const DescHi& hi) {
  asm volatile(
      "{.reg .pred p; .reg .b64 da, db; setp.ne.b32 p, %50, 0; mov.b64 da, {%48, %53}; mov.b64 db, {%49, %54};\n"
      "wgmma.mma_async.sync.aligned.m64n96k16.f32.bf16.bf16 "
      "{%0,%1,%2,%3,%4,%5,%6,%7,%8,%9,%10,%11,%12,%13,%14,%15,%16,%17,%18,%19,%20,%21,%22,%23,%24,%25,%26,%27,%28,%29,%30,%31,%32,%33,%34,%35,%36,%37,%38,%39,%40,%41,%42,%43,%44,%45,%46,%47},"
      " da, db, p, 1, 1, %51, %52;}\n"
      : "+f"(d[0]), "+f"(d[1]), "+f"(d[2]), "+f"(d[3]), "+f"(d[4]), "+f"(d[5]), "+f"(d[6]), "+f"(d[7]), "+f"(d[8]), "+f"(d[9]), "+f"(d[10]), "+f"(d[11]), "+f"(d[12]), "+f"(d[13]), "+f"(d[14]), "+f"(d[15]), "+f"(d[16]), "+f"(d[17]), "+f"(d[18]), "+f"(d[19]), "+f"(d[20]), "+f"(d[21]), "+f"(d[22]), "+f"(d[23]), "+f"(d[24]), "+f"(d[25]), "+f"(d[26]), "+f"(d[27]), "+f"(d[28]), "+f"(d[29]), "+f"(d[30]), "+f"(d[31]), "+f"(d[32]), "+f"(d[33]), "+f"(d[34]), "+f"(d[35]), "+f"(d[36]), "+f"(d[37]), "+f"(d[38]), "+f"(d[39]), "+f"(d[40]), "+f"(d[41]), "+f"(d[42]), "+f"(d[43]), "+f"(d[44]), "+f"(d[45]), "+f"(d[46]), "+f"(d[47])
      : "r"(da), "r"(db), "r"(scale_d), "n"(TA), "n"(TB), "r"(hi.sw), "r"(TB ? hi.img : hi.sw2));
}
template <int TA, int TB>
__device__ __forceinline__ void wgmma96_first(float (&d)[48], uint32_t da, uint32_t db, const DescHi& hi) {
  asm volatile(
      "{.reg .pred p; .reg .b64 da, db; setp.ne.b32 p, 0, 0; mov.b64 da, {%48, %52}; mov.b64 db, {%49, %53};\n"
      "wgmma.mma_async.sync.aligned.m64n96k16.f32.bf16.bf16 "
      "{%0,%1,%2,%3,%4,%5,%6,%7,%8,%9,%10,%11,%12,%13,%14,%15,%16,%17,%18,%19,%20,%21,%22,%23,%24,%25,%26,%27,%28,%29,%30,%31,%32,%33,%34,%35,%36,%37,%38,%39,%40,%41,%42,%43,%44,%45,%46,%47},"
      " da, db, p, 1, 1, %50, %51;}\n"
      : "=f"(d[0]), "=f"(d[1]), "=f"(d[2]), "=f"(d[3]), "=f"(d[4]), "=f"(d[5]), "=f"(d[6]), "=f"(d[7]), "=f"(d[8]), "=f"(d[9]), "=f"(d[10]), "=f"(d[11]), "=f"(d[12]), "=f"(d[13]), "=f"(d[14]), "=f"(d[15]), "=f"(d[16]), "=f"(d[17]), "=f"(d[18]), "=f"(d[19]), "=f"(d[20]), "=f"(d[21]), "=f"(d[22]), "=f"(d[23]), "=f"(d[24]), "=f"(d[25]), "=f"(d[26]), "=f"(d[27]), "=f"(d[28]), "=f"(d[29]), "=f"(d[30]), "=f"(d[31]), "=f"(d[32]), "=f"(d[33]), "=f"(d[34]), "=f"(d[35]), "=f"(d[36]), "=f"(d[37]), "=f"(d[38]), "=f"(d[39]), "=f"(d[40]), "=f"(d[41]), "=f"(d[42]), "=f"(d[43]), "=f"(d[44]), "=f"(d[45]), "=f"(d[46]), "=f"(d[47])
      : "r"(da), "r"(db), "n"(TA), "n"(TB), "r"(hi.sw), "r"(TB ? hi.img : hi.sw2));
}

__device__ __forceinline__ uint32_t pack_bf16(float lo, float hi) {
  uint32_t r; asm("cvt.rn.bf16x2.f32 %0, %1, %2;" : "=r"(r) : "f"(hi), "f"(lo)); return r;
}
__device__ __forceinline__ float ex2(float x) { float y; asm("ex2.approx.ftz.f32 %0, %1;" : "=f"(y) : "f"(x)); return y; }
__device__ __forceinline__ void stsm4(uint32_t addr, uint32_t a, uint32_t b, uint32_t c, uint32_t d) {
  asm volatile("stmatrix.sync.aligned.m8n8.x4.shared.b16 [%0], {%1,%2,%3,%4};" ::"r"(addr), "r"(a), "r"(b), "r"(c), "r"(d) : "memory");
}
__device__ __forceinline__ void stsm4_t(uint32_t addr, uint32_t a, uint32_t b, uint32_t c, uint32_t d) {
  asm volatile("stmatrix.sync.aligned.m8n8.x4.trans.shared.b16 [%0], {%1,%2,%3,%4};" ::"r"(addr), "r"(a), "r"(b), "r"(c), "r"(d) : "memory");
}
template <int N> __device__ __forceinline__ void bar_sync(int id) { asm volatile("bar.sync %0, %1;" ::"r"(id), "n"(N) : "memory"); }
template <int N> __device__ __forceinline__ void bar_arrive(int id) { asm volatile("bar.arrive %0, %1;" ::"r"(id), "n"(N) : "memory"); }
__device__ __forceinline__ bool bar_or128(int id, bool v) {
  uint32_t r;
  asm volatile("{.reg .pred p, q; setp.ne.b32 p, %2, 0; bar.red.or.pred q, %1, 128, p; selp.u32 %0, 1, 0, q;}"
               : "=r"(r) : "r"(id), "r"((uint32_t)v) : "memory");
  return r;
}
__device__ __forceinline__ void stg32(void* p, uint32_t v) { asm volatile("st.global.u32 [%0], %1;" ::"l"(p), "r"(v) : "memory"); }
__device__ __forceinline__ void sts32(uint32_t addr, uint32_t v) { asm volatile("st.shared.u32 [%0], %1;" ::"r"(addr), "r"(v) : "memory"); }
__device__ __forceinline__ uint32_t lds32(uint32_t addr) { uint32_t v; asm volatile("ld.shared.u32 %0, [%1];" : "=r"(v) : "r"(addr) : "memory"); return v; }
__device__ __forceinline__ float2 lds64f(uint32_t addr) {
  float2 v; asm volatile("ld.shared.v2.f32 {%0,%1}, [%2];" : "=f"(v.x), "=f"(v.y) : "r"(addr) : "memory"); return v;
}
__device__ __forceinline__ void col_reduce(const float (&v)[24], float (&r)[3], int lane) {
  float a[12], b[6];
  const bool h16 = lane & 16, h8 = lane & 8, h4 = lane & 4;
#pragma unroll
  for (int i = 0; i < 12; i++) {
    float keep = h16 ? v[12 + i] : v[i], send = h16 ? v[i] : v[12 + i];
    float o = __shfl_xor_sync(0xffffffffu, send, 16);
    a[i] = keep + o;
  }
#pragma unroll
  for (int i = 0; i < 6; i++) {
    float keep = h8 ? a[6 + i] : a[i], send = h8 ? a[i] : a[6 + i];
    float o = __shfl_xor_sync(0xffffffffu, send, 8);
    b[i] = keep + o;
  }
#pragma unroll
  for (int i = 0; i < 3; i++) {
    float keep = h4 ? b[3 + i] : b[i], send = h4 ? b[i] : b[3 + i];
    float o = __shfl_xor_sync(0xffffffffu, send, 4);
    r[i] = keep + o;
  }
}
__device__ __forceinline__ int col_of(int lane, int i) {
  int c = 12 * ((lane >> 4) & 1) + 6 * ((lane >> 3) & 1) + 3 * ((lane >> 2) & 1) + i;
  return 8 * (c >> 1) + 2 * (lane & 3) + (c & 1);
}

struct Tid {
  int tid, t, w, warp, lane;
  __device__ __forceinline__ Tid() {
    asm volatile("mov.u32 %0, %%tid.x;" : "=r"(tid));
    const int wi = __shfl_sync(0xffffffffu, tid >> 5, 0);
    t = tid & 127; w = wi >> 2; warp = wi & 3; lane = tid & 31;
  }
};

struct Ctx {
  uint32_t sb;
  int br, idx, rank;
  uint32_t seq0;
  uint32_t pol;
};
__device__ __forceinline__ unsigned char* scratch_base() {
  return reinterpret_cast<unsigned char*>((reinterpret_cast<uintptr_t>(g_scratch_raw) + (1u << 21) - 1) & ~(uintptr_t)((1u << 21) - 1));
}
__device__ __forceinline__ uint32_t chunk_par(uint32_t off) { return ((off >> 12) ^ (off >> 13) ^ (off >> 16) ^ (off >> 17) ^ (off >> 19)) & 1; }
__device__ __forceinline__ int tile_id(int h, int b) { return b * RING_H + (h % RING_H); }
__device__ __forceinline__ uint32_t tile_pol(const Ctx& c, int tile) {
  return chunk_par((uint32_t)tile * TILE_SPAN) ^ ((c.pol >> (tile >> 5)) & 1) ^ c.br;
}
__device__ __forceinline__ unsigned char* tile_step(int tile, int k, uint32_t pol) {
  return scratch_base() + (size_t)tile * TILE_SPAN + k * 8192 + (((k & 1) ^ pol) << 12);
}

enum { FL_Q = 0, FL_O = 1, FL_DONE = 2   };
__device__ __forceinline__ uint32_t* tile_flag(const Ctx& c, int tile, int which) {
  return reinterpret_cast<uint32_t*>(tile_step(tile, 0, tile_pol(c, tile)) + KSTEP + 128 * (1 + which));
}

template <bool B> struct BoolC { static constexpr bool value = B; };

struct Ring {
  uint32_t s, ph;
  template <int N> __device__ __forceinline__ void next() { if (++s == N) { s = 0; ph ^= 1; } }
  __device__ __forceinline__ void next_o(uint32_t i) { if (++s == (i < GO_SWITCH ? GO_N : GO_N2)) { s = 0; ph ^= 1; } }
};

constexpr float SM_C = 0.08838834764831845f * 1.4426950408889634f;
constexpr float SM_LIMIT = 18446744073709551616.0f;

__device__ __forceinline__ void att_producer(const Params& p, const Ctx& c, int a, int n_items, int isv) {
  const uint64_t pol = policy_evict_first();
  const uint32_t sb = c.sb, bars = sb + MISC_BAR;
  const CUtensorMap* m = (isv ? p.v : p.k) + c.br;
  const bool local = a < p.n_local;
  auto row_of = [&](int n) {
    const int item = a + n * p.n_att;
    return ((item & 15) * NH + (item >> 4)) * SK;
  };
  auto unit_row = [&](int row, uint32_t g) { return row + 64 * (int)((g + 4 * c.br) & 7); };
  if (isv && local) {
    const int h = a >> 4, b = a & 15;
#pragma unroll 1
    for (int kc = 0; kc < 10; kc++) {
      const int st = kc & 7;
      if (kc >= 8) mbar_wait_slow_w(bars + 8 * (B_EMPTY2 + st), 0);
      if (elect_one()) {
        const uint32_t wdst = sb + ((st + 4) & 7) * UNIT;
        mbar_expect_tx(bars + 8 * (B_FULL2 + st), 16384 + 12288);
        tma2d(sb + ATT_Q + st * 12288, &p.x[c.br], kc * 64, b * SQ, bars + 8 * (B_FULL2 + st));
        if (kc < 8) tma2d_mc(wdst + c.rank * 8192, &p.wq[c.br], h * DH + c.rank * 64, kc * 64, bars + 8 * (B_FULL2 + st));
        else {
          tma2d(wdst, &p.wq[c.br], h * DH, kc * 64, bars + 8 * (B_FULL2 + st));
          tma2d(wdst + 8192, &p.wq[c.br], h * DH + 64, kc * 64, bars + 8 * (B_FULL2 + st));
        }
      }
    }
  }
  const uint32_t bar0 = bars + 32 * isv, dst0 = sb + 4 * isv * UNIT;
  int row = row_of(0);
#pragma unroll 1
  for (int u = 0; u < 4; u++) {
    if (local) mbar_wait_slow_w(bars + 8 * (B_EMPTY2 + (isv ? u : u + 4)), isv && u < 2);
    if (elect_one()) {
      mbar_expect_tx(bar0 + 8 * u + 8 * B_FULL, UNIT);
      tma3d(dst0 + u * UNIT, m, 0, unit_row(row, u), 0, bar0 + 8 * u + 8 * B_FULL, pol);
    }
  }
  uint32_t* prog = &g_prog[(((c.seq0 / NH) & 1) * 2 + isv) * 32] + (threadIdx.x & 31);
  const int weight = 2 * NB * NH * 256 / n_items;
  const int band = p.n_att / 2;
  uint32_t seen = weight >> 9;
  const int grade = (2 * (NH - 1 - ((a + (n_items - 1) * p.n_att) >> 4)) - 1) * GRADE * p.n_att / 8;
  const bool heavy = n_items > p.items_base;
  uint32_t cap = 3;
  const uint32_t g_end = 8 * n_items;
#pragma unroll 1
  for (uint32_t g = 4; g < g_end; g++) {
    if ((g & 7) == 0) row = row_of(g >> 3);
    const uint32_t bar = bar0 + 8 * (g & 3), dst = dst0 + (g & 3) * UNIT, r = unit_row(row, g);
    mbar_wait_slow_w(bar0 + 8 * ((g - cap) & 3) + 8 * B_FULL, ((g - cap) >> 2) & 1);
    mbar_wait_slow_w(bar + 8 * B_EMPTY, ((g >> 2) & 1) ^ 1);
    if (elect_one()) {
      mbar_expect_tx(bar + 8 * B_FULL, UNIT);
      tma3d(dst, m, 0, r, 0, bar + 8 * B_FULL, pol);
    }
    if (g & 1) {
      const int lead = (((int)(g - 6) * weight) >> 9) - (int)__shfl_sync(0xffffffffu, seen, 0) - (grade * (int)min(g, 64u) >> 6);
      if (g > 5) cap = 2 * lead > band * (heavy ? FREE : 1) ? 2 : 4;
      const uint32_t g2 = g + (heavy ? AHEAD_H : AHEAD);
      const int thr = !local ? 0 : g + ENDN >= g_end ? AHEAD_E : 2 * AHEAD_T;
      if ((2 * lead < -thr * band || (heavy && cap == 4)) && g2 + 1 < g_end && elect_one()) {
        tma3d_prefetch_pol(m, 0, unit_row(row_of(g2 >> 3), g2), 0, pol);
        tma3d_prefetch_pol(m, 0, unit_row(row_of((g2 + 1) >> 3), g2 + 1), 0, pol);
      }
      asm volatile("{.reg .pred q; setp.eq.u32 q, %2, 0; @q atom.relaxed.gpu.global.inc.u32 %0, [%1], 0x7fffffff;}"
                   : "+r"(seen) : "l"(prog), "r"(threadIdx.x & 31));
    }
  }
}

__device__ __forceinline__ void att_qloader(const Params& p, const Ctx& c, int a, int n_items) {
  const uint32_t sb = c.sb, bars = sb + MISC_BAR;
  for (int n = a < p.n_local; n < n_items; n++) {
    const int item = a + n * p.n_att, tile = tile_id(item >> 4, item & 15);
    const uint32_t pl = tile_pol(c, tile);
    flag_wait(tile_flag(c, tile, FL_Q), c.seq0 + (item >> 4));
    fence_async_global();
    if (n >= 2) bar_sync<160>(NB_QE);
    else if (n == 1 && a < p.n_local) mbar_wait_slow_w(bars + 8 * B_QF, 0);
    if (elect_one()) {
      mbar_expect_tx(bars + 8 * (B_QF + (n & 1)), IMG);
      tma4d(sb + ATT_Q + (n & 1) * IMG, &p.tile[pl], tile * 4, bars + 8 * (B_QF + (n & 1)));
    }
    __syncwarp();
  }
}

__device__ __forceinline__ void att_flags(const Params& p, const Ctx& c, int a, int n_items) {
  for (int n = 0; n < n_items; n++) {
    const int item = a + n * p.n_att, tile = tile_id(item >> 4, item & 15);
    mbar_wait_slow_w(c.sb + MISC_BAR + 8 * (B_ODONE + (n & 3)), (n >> 2) & 1);
    if (elect_one()) st_release(tile_flag(c, tile, FL_O), c.seq0 + (item >> 4));
    __syncwarp();
  }
}

__device__ __forceinline__ void att_softmax_wg(const Params& p, uint32_t sb, int n_items) {
  const DescHi hi{p.hi_sw, p.hi_sw2, p.hi_img};
  const Tid T; const int W = T.w, warp = T.warp, lane = T.lane;
  const uint32_t bars = sb + MISC_BAR;
  float s[48], x[48], mc[24], l[24];
  const uint32_t p_st = sb + ATT_P + W * PUNIT + warp * KSTEP + ((lane >> 3) & 1) * 1536 + (lane >> 4) * 128 + (lane & 7) * 16;
  const uint32_t col_off = (lane & 3) * 8;
  const uint32_t kbar = bars + 8 * W;
  const uint32_t kdesc = desc_sw128(sb + ATT_K + W * UNIT), qdesc = desc_img(sb + ATT_Q);
#pragma unroll
  for (int c = 0; c < 24; c++) l[c] = 0.f;

  auto make_ref = [&]() {
    const uint32_t mx = sb + ATT_MX;
    if (W == 0) {
      float v[6];
      auto pick = [&](int j0) {
#pragma unroll
        for (int k = 0; k < 6; k++) v[k] = fmaxf(s[4 * (j0 + (k >> 1)) + (k & 1)], s[4 * (j0 + (k >> 1)) + 2 + (k & 1)]);
      };
      if (warp == 0) pick(0); else if (warp == 1) pick(3); else if (warp == 2) pick(6); else pick(9);
#pragma unroll
      for (int o = 4; o < 32; o <<= 1)
#pragma unroll
        for (int k = 0; k < 6; k++) v[k] = fmaxf(v[k], __shfl_xor_sync(0xffffffffu, v[k], o));
      if (lane < 4) {
#pragma unroll
        for (int k = 0; k < 3; k++)
          asm volatile("st.shared.v2.f32 [%0], {%1, %2};" ::"r"(mx + col_off + warp * 96 + k * 32), "f"(v[2 * k] * SM_C), "f"(v[2 * k + 1] * SM_C) : "memory");
      }
      bar_arrive<256>(NB_MX);
    }
  };
  auto load_ref = [&]() {
    if (W == 0) bar_sync<128>(NB_WG0); else bar_sync<256>(NB_MX);
#pragma unroll
    for (int j = 0; j < 12; j++) { const float2 q = lds64f(sb + ATT_MX + col_off + 32 * j); mc[2 * j] = q.x; mc[2 * j + 1] = q.y; }
  };
  auto scale_scores = [&]() {
    reg_fence(s);
#pragma unroll
    for (int c = 0; c < 48; c++) x[c] = fmaf(s[c], SM_C, -mc[2 * (c >> 2) + (c & 1)]);
    reg_fence(x);
  };
  auto exp_store = [&](auto with_s, uint32_t g) {
    constexpr bool WITH_S = decltype(with_s)::value;
    bar_sync<256>(NB_PE + W + 2 * (g & 1));
    const uint32_t dst = p_st + (g & 1) * (2 * PUNIT);
    const uint32_t da = kdesc + ((g + 1) & 1) * (2 * UNIT >> 4);
    const uint32_t db = qdesc + (((g + 1) >> 2) & 1) * (IMG >> 4);
    if (WITH_S) wg_fence();
#pragma unroll
    for (int q = 0; q < 6; q++) {
      if (WITH_S && q < S_SPLIT) {
#pragma unroll
        for (int kk = q * (8 / S_SPLIT); kk < (q + 1) * (8 / S_SPLIT); kk++) {
          if (kk == 0) wgmma96_first<0, 1>(s, da, db, hi);
          else wgmma96<0, 1>(s, da + (((kk >> 2) * 8192 + (kk & 3) * 32) >> 4), db + ((kk * KSTEP) >> 4), 1, hi);
        }
        if (q == S_SPLIT - 1) wg_commit();
      }
      float e[8];
#pragma unroll
      for (int k = 0; k < 8; k++) e[k] = ex2(x[8 * q + k]);
      l[4 * q + 0] += e[0] + e[2];
      l[4 * q + 1] += e[1] + e[3];
      l[4 * q + 2] += e[4] + e[6];
      l[4 * q + 3] += e[5] + e[7];
      stsm4(dst + q * 256, pack_bf16(e[0], e[1]), pack_bf16(e[2], e[3]), pack_bf16(e[4], e[5]), pack_bf16(e[6], e[7]));
    }
  };
  auto publish = [&](uint32_t g) {
    fence_async_smem();
    bar_arrive<256>(NB_PF + W + 2 * (g & 1));
  };
  auto last_unit = [&]() {
    float rr[3];
    col_reduce(l, rr, lane);
    if (W == 1) {
      bar_sync<256>(NB_L0);
#pragma unroll
      for (int k = 0; k < 3; k++) rr[k] += __uint_as_float(lds32(sb + ATT_LP + warp * 384 + 4 * col_of(lane, k)));
    }
#pragma unroll
    for (int k = 0; k < 3; k++) sts32(sb + ATT_LP + warp * 384 + 4 * col_of(lane, k), __float_as_uint(rr[k]));
    bar_arrive<256>(W ? NB_L : NB_L0);
#pragma unroll
    for (int c = 0; c < 24; c++) l[c] = 0.f;
  };

  const uint32_t g_last = 4 * n_items - 1;
  mbar_wait_w(bars + 8 * B_QF, 0);
  mbar_wait_w(kbar + 8 * B_FULL, 0);
  wg_fence();
  wgmma96_first<0, 1>(s, kdesc, qdesc, hi);
#pragma unroll
  for (int kk = 1; kk < 8; kk++)
    wgmma96<0, 1>(s, kdesc + (((kk >> 2) * 8192 + (kk & 3) * 32) >> 4), qdesc + ((kk * KSTEP) >> 4), 1, hi);
  wg_commit();
  wg_wait<0>();
  if (lane == 0) mbar_arrive(kbar + 8 * B_EMPTY);
  reg_fence(s);
  make_ref();
  load_ref();
  scale_scores();
  bool ready = false;
#pragma unroll 1
  for (uint32_t g = 0; g != g_last; g++) {
    const uint32_t gn = g + 1;
    const uint32_t kb = kbar + 16 * (gn & 1);
    if (__builtin_expect(!__all_sync(0xffffffffu, ready), 0)) {
      if ((gn & 3) == 0) mbar_wait_w(bars + 8 * (B_QF + ((gn >> 2) & 1)), (gn >> 3) & 1);
      mbar_wait_w(kb + 8 * B_FULL, (gn >> 1) & 1);
    }
    exp_store(BoolC<true>{}, g);
    ready = mbar_test(kbar + 16 * (g & 1) + 8 * B_FULL, ((gn + 1) >> 1) & 1) && (gn & 3) != 3;
    if (__builtin_expect((gn & 3) == 0, 0)) {
      wg_wait<0>();
      if (lane == 0) mbar_arrive(kb + 8 * B_EMPTY);
      reg_fence(s);
      make_ref();
      publish(g);
      last_unit();
      load_ref();
      scale_scores();
    } else {
      wg_wait<0>();
      if (lane == 0) mbar_arrive(kb + 8 * B_EMPTY);
      scale_scores();
      publish(g);
    }
  }
  exp_store(BoolC<false>{}, g_last);
  publish(g_last);
  last_unit();
}

__device__ __forceinline__ void att_fallback(const __nv_bfloat16* kp, const __nv_bfloat16* vp, uint32_t qimg,
                                             uint32_t sb, unsigned char* ostep, int q, int t) {
  const uint32_t fq = sb + ATT_LP, fs = fq + 512, fr = fs + 512;
  const uint32_t eoff = ((t >> 3) & 1) * 1536 + (q >> 3) * 128 + (t & 7) * 16 + (q & 7) * 2;
  unsigned short qraw;
  asm volatile("ld.shared.u16 %0, [%1];" : "=h"(qraw) : "r"(qimg + (t >> 4) * KSTEP + eoff) : "memory");
  sts32(fq + 4 * t, (uint32_t)qraw << 16);
  bar_sync<128>(NB_WG2);
  float sc[4] = {0.f, 0.f, 0.f, 0.f};
#pragma unroll 2
  for (int d = 0; d < DH; d += 8) {
    uint4 kv[4];
#pragma unroll
    for (int r = 0; r < 4; r++) kv[r] = __ldg(reinterpret_cast<const uint4*>(kp + (size_t)(t + 128 * r) * DH + d));
#pragma unroll
    for (int i = 0; i < 4; i++) {
      const float2 qq = lds64f(fq + 4 * d + 8 * i);
#pragma unroll
      for (int r = 0; r < 4; r++) {
        const uint32_t w = i == 0 ? kv[r].x : i == 1 ? kv[r].y : i == 2 ? kv[r].z : kv[r].w;
        sc[r] = fmaf(qq.x, __uint_as_float(w << 16), sc[r]);
        sc[r] = fmaf(qq.y, __uint_as_float(w & 0xffff0000u), sc[r]);
      }
    }
  }
  float mx = fmaxf(fmaxf(sc[0], sc[1]), fmaxf(sc[2], sc[3]));
  for (int o = 16; o; o >>= 1) mx = fmaxf(mx, __shfl_xor_sync(0xffffffffu, mx, o));
  if ((t & 31) == 0) sts32(fr + 4 * (t >> 5), __float_as_uint(mx));
  bar_sync<128>(NB_WG2);
  for (int i = 0; i < 4; i++) mx = fmaxf(mx, __uint_as_float(lds32(fr + 4 * i)));
  float sum = 0.f, a = 0.f;
#pragma unroll 1
  for (int r = 0; r < 4; r++) {
    sts32(fs + 4 * t, __float_as_uint(ex2(((r == 0 ? sc[0] : r == 1 ? sc[1] : r == 2 ? sc[2] : sc[3]) - mx) * SM_C)));
    bar_sync<128>(NB_WG2);
#pragma unroll 1
    for (int k0 = 0; k0 < 128; k0 += 32) {
      unsigned short vv[32];
#pragma unroll
      for (int k = 0; k < 32; k++) vv[k] = __ldg(reinterpret_cast<const unsigned short*>(vp) + (size_t)(128 * r + k0 + k) * DH + t);
#pragma unroll
      for (int k = 0; k < 32; k++) {
        const float e = __uint_as_float(lds32(fs + 4 * (k0 + k)));
        sum += e;
        a = fmaf(e, __uint_as_float((uint32_t)vv[k] << 16), a);
      }
    }
    bar_sync<128>(NB_WG2);
  }
  const unsigned short res = __bfloat16_as_ushort(__float2bfloat16(a / sum));
  *reinterpret_cast<unsigned short*>(ostep + eoff) = res;
  bar_sync<128>(NB_WG2);
}

__device__ __forceinline__ void att_pv_wg(const Params& p, const Ctx& c, int a, int n_items) {
  const uint32_t sb = c.sb;
  const DescHi hi{p.hi_sw, p.hi_sw2, p.hi_img};
  const Tid T; const int t = T.t, warp = T.warp, lane = T.lane;
  const uint32_t bars = sb + MISC_BAR;
  float o[2][48];
  const uint32_t col_off = (lane & 3) * 8;
  const uint32_t o_st = sb + ATT_Q + warp * KSTEP + ((lane >> 3) & 1) * 1536 + (lane >> 4) * 128 + (lane & 7) * 16;
  const uint32_t vdesc = desc_sw128(sb + ATT_V), pdesc = desc_img(sb + ATT_P);
  if (a < p.n_local) {
#pragma unroll 1
    for (int kc = 0; kc < 10; kc++) {
      const int st = kc & 7;
      mbar_wait_w(bars + 8 * (B_FULL2 + st), kc >> 3);
      const uint32_t da = desc_sw128(sb + ((st + 4) & 7) * UNIT);
      const uint32_t db = desc_sw128(sb + ATT_Q + st * 12288);
      wg_fence();
#pragma unroll
      for (int kk = 0; kk < 4; kk++)
#pragma unroll
        for (int m = 0; m < 2; m++)
          wgmma96<1, 0>(o[m], da + ((m * 8192 + kk * 2048) >> 4), db + ((kk * 32) >> 4), (kc | kk) != 0, hi);
      wg_commit();
      wg_wait<1>();
      if (kc > 0 && lane == 0) mbar_arrive(bars + 8 * (B_EMPTY2 + ((kc - 1) & 7)));
    }
    wg_wait<0>();
    if (lane == 0) mbar_arrive(bars + 8 * (B_EMPTY2 + 1));
    bar_sync<128>(NB_WG2);
    reg_fence(o[0]); reg_fence(o[1]);
#pragma unroll
    for (int m = 0; m < 2; m++)
#pragma unroll
      for (int g = 0; g < 6; g++) {
        const float* d = &o[m][8 * g];
        stsm4(o_st + m * PUNIT + g * 256, pack_bf16(d[0], d[1]), pack_bf16(d[2], d[3]),
              pack_bf16(d[4], d[5]), pack_bf16(d[6], d[7]));
      }
    fence_async_smem();
    bar_sync<128>(NB_WG2);
    if (t == 0) mbar_arrive(bars + 8 * B_QF);
  }
#pragma unroll
  for (int i = 0; i < NP; i++) bar_arrive<256>(NB_PE + i);
  const uint32_t g_end = 8 * n_items;
  uint32_t g = 0;
  auto release = [&](uint32_t gg) {
    if (gg + NP < g_end) bar_arrive<256>(NB_PE + (gg & 3));
    if (lane == 0) mbar_arrive(bars + 8 * (B_EMPTY + 4 + (gg & 3)));
  };
  auto issue_pv = [&](auto first) {
    bar_sync<256>(NB_PF + (g & 3));
    wg_fence();
    const uint32_t da = vdesc + (g & 3) * (UNIT >> 4);
    const uint32_t db = pdesc + (g & 3) * (PUNIT >> 4);
#pragma unroll
    for (int kk = 0; kk < 4; kk++)
#pragma unroll
      for (int m = 0; m < 2; m++) {
        if (decltype(first)::value && kk == 0) wgmma96_first<1, 1>(o[m], da + ((m * 8192) >> 4), db, hi);
        else wgmma96<1, 1>(o[m], da + ((m * 8192 + kk * 2048) >> 4), db + ((kk * KSTEP) >> 4), 1, hi);
      }
    wg_commit();
    g++;
  };
  for (int n = 0; n < n_items; n++) {
    mbar_wait_w(bars + 8 * (B_FULL + 4), 0);
    issue_pv(BoolC<true>{});
#pragma unroll 1
    do {
      const uint32_t vb = bars + 8 * (B_FULL + 4 + (g & 3));
      bool held = true;
      if (__builtin_expect(!__all_sync(0xffffffffu, mbar_test(vb, (g >> 2) & 1)), 0)) {
        wg_wait<0>(); release(g - 1); held = false;
        mbar_wait_slow_w(vb, (g >> 2) & 1);
      }
      issue_pv(BoolC<false>{});
      wg_wait<1>();
      if (held) release(g - 2);
    } while (g & 7);
    bool bad = false;
    bar_sync<256>(NB_L);
    if (warp < 3) {
      float sum = 0.f;
#pragma unroll
      for (int i = 0; i < 4; i++) sum += __uint_as_float(lds32(sb + ATT_LP + i * 384 + 4 * t));
      bad = !(sum < SM_LIMIT && sum > 1.0f / SM_LIMIT);
      float inv; asm("rcp.approx.ftz.f32 %0, %1;" : "=f"(inv) : "f"(sum));
      sts32(sb + ATT_LINV + 4 * t, bad ? 0u : __float_as_uint(inv));
    }
    wg_wait<0>();
    reg_fence(o[0]); reg_fence(o[1]);
    release(g - 1);
    bad = __any_sync(0xffffffffu, bar_or128(NB_WG2R, bad));
    const int item = a + n * p.n_att, tile = tile_id(item >> 4, item & 15);
    const uint32_t pl = tile_pol(c, tile);
    if (!bad && n + 2 < n_items) bar_arrive<160>(NB_QE);
    unsigned char* d0 = tile_step(tile, warp, pl) + lane * 4;
    unsigned char* d1 = d0 + 4 * 8192;
#pragma unroll
    for (int j = 0; j < 12; j++) {
      const float2 q = lds64f(sb + ATT_LINV + col_off + 32 * j);
      stg32(d0 + j * 128, pack_bf16(o[0][4 * j] * q.x, o[0][4 * j + 1] * q.y));
      stg32(d0 + 1536 + j * 128, pack_bf16(o[0][4 * j + 2] * q.x, o[0][4 * j + 3] * q.y));
      stg32(d1 + j * 128, pack_bf16(o[1][4 * j] * q.x, o[1][4 * j + 1] * q.y));
      stg32(d1 + 1536 + j * 128, pack_bf16(o[1][4 * j + 2] * q.x, o[1][4 * j + 3] * q.y));
    }
    if (__builtin_expect(bad, 0)) {
      const size_t kvoff = (size_t)((item & 15) * NH + (item >> 4)) * SK * DH;
#pragma unroll 1
      for (int q = 0; q < SQ; q++)
        if (__all_sync(0xffffffffu, lds32(sb + ATT_LINV + 4 * q) == 0u))
          att_fallback(p.kp[c.br] + kvoff, p.vp[c.br] + kvoff, sb + ATT_Q + (n & 1) * IMG, sb, tile_step(tile, t >> 4, pl), q, t);
      if (n + 2 < n_items) bar_arrive<160>(NB_QE);
    }
    __syncwarp();
    if (lane == 0) mbar_arrive(bars + 8 * (B_ODONE + (n & 3)));
  }
}

constexpr int GO_PF = 2;

__device__ __forceinline__ void gq_producer(const Params& p, const Ctx& c) {
  const uint32_t sb = c.sb, bars = sb + MISC_BAR;
  const int sub = c.idx & 1, b = (c.idx >> 1) * 2 + c.rank;
  const int h0 = p.n_local / NB, n_chunks = (NH - h0) / 2 * 10;
  const unsigned char* wrow = p.wqp[c.br] + (size_t)(c.idx * 2 + c.rank) * (NH * DH * 2);
  int col = (h0 + sub) * DH + c.rank * 64, kc = 0;
  int pos = h0 * 5;
  Ring r{0, 1};
#pragma unroll 1
  for (int i = 0; i < n_chunks; i++) {
    uint32_t fb, dst, xdst = 0;
    if (i < 2) { fb = bars + 8 * (B_GXF + i); dst = sb + G_O + i * GQ_STAGE; }
    else {
      mbar_wait_slow_w(bars + 8 * (B_GQE + r.s), r.ph);
      fb = bars + 8 * (B_GQF + r.s); dst = sb + G_Q + r.s * 16384;
      xdst = sb + G_XS + (r.s >> 1) * 12288;
      r.next<GQ_N>();
    }
    if (i < 2) xdst = dst + 16384;
    if (!(kc & 1)) xdst = sb + G_XR + (kc >> 1) * 12288;
    const bool lx = (kc & 1) || i < 10;
    if (elect_one()) {
      mbar_expect_tx(fb, lx ? GQ_STAGE : 16384);
      tma2d_mc(dst + c.rank * 8192, &p.wq[c.br], col, kc * 64, fb);
      if (lx) tma2d(xdst, &p.x[c.br], kc * 64, b * SQ, fb);
    }
    if (++kc == 10) { kc = 0; col += 2 * DH; }
    const int grp = (pos + WQ_M) / (5 * WQ_G) + 1, left = grp * 5 * WQ_G - pos - WQ_M;
    if (grp < NH / WQ_G && grp * WQ_G >= WQ_G0 && left > 0 && left <= 20 && elect_one())
      bulk_prefetch(wrow + (size_t)(20 - left) * 32 * (NH * DH * 2) + grp * WQ_G * DH * 2, WQ_G * DH * 2);
    pos++;
  }
}

__device__ __forceinline__ void gq_flags(const Params& p, const Ctx& c) {
  const int sub = c.idx & 1, b = (c.idx >> 1) * 2 + c.rank;
  for (int h = p.n_local / NB + sub; h < NH; h += 2) {
    if (h >= RING_H) {
      flag_wait(tile_flag(c, tile_id(0, b), FL_DONE + (threadIdx.x & 1)), c.seq0 + h - RING_H);
    }
    bar_arrive<160>(NB_GSLOT);
    bar_sync<160>(NB_GDONE);
    const int tile = tile_id(h, b);
    if (elect_one()) st_release(tile_flag(c, tile, FL_Q), c.seq0 + h);
    __syncwarp();
  }
}

__device__ __forceinline__ void gq_consumer(const Params& p, const Ctx& c) {
  const DescHi hi{p.hi_sw, p.hi_sw2, p.hi_img};
  const Tid T; const int warp = T.warp, lane = T.lane;
  const uint32_t sb = c.sb, bars = sb + MISC_BAR;
  const int sub = c.idx & 1, b = (c.idx >> 1) * 2 + c.rank;
  const uint32_t desc0 = desc_sw128(sb + G_Q);
  float d[2][48];
  Ring r{0, 0};
  uint32_t prev = 0;
  auto release = [&](uint32_t j) { if (lane < 2) mbar_arrive_cluster(bars + 8 * (B_GQE + j), lane); };
  const uint32_t xsdesc = desc_sw128(sb + G_XS), xrdesc = desc_sw128(sb + G_XR);
  auto adesc = [&]() { return desc0 + r.s * (16384 >> 4); };
  auto bdesc = [&](int kc) { return (kc & 1) ? xsdesc + (r.s >> 1) * (12288 >> 4) : xrdesc + (kc >> 1) * (12288 >> 4); };
  auto issue = [&](auto first, uint32_t da, uint32_t db) {
    wg_fence();
#pragma unroll
    for (int kk = 0; kk < 4; kk++)
#pragma unroll
      for (int m = 0; m < 2; m++) {
        if (decltype(first)::value && kk == 0) wgmma96_first<1, 0>(d[m], da + ((m * 8192) >> 4), db, hi);
        else wgmma96<1, 0>(d[m], da + ((m * 8192 + kk * 2048) >> 4), db + ((kk * 32) >> 4), 1, hi);
      }
    wg_commit();
  };
  uint32_t pk[48];
  unsigned char* dst = nullptr;
  auto store_part = [&](int part) {
#pragma unroll
    for (int i = 0; i < 48; i++)
      if (i / 16 == part) stg32(dst + (i / 24) * (4 * 8192) + (i & 1) * 1536 + ((i % 24) >> 1) * 128, pk[i]);
  };
  bool pending = false;
  for (int h = p.n_local / NB + sub; h < NH; h += 2) {
    int kc = 1;
    if (h < p.n_local / NB + 2) {
      mbar_wait_w(bars + 8 * B_GXF, 0);
      issue(BoolC<true>{}, desc_sw128(sb + G_O), xrdesc);
      mbar_wait_w(bars + 8 * (B_GXF + 1), 0);
      issue(BoolC<false>{}, desc_sw128(sb + G_O + GQ_STAGE), desc_sw128(sb + G_O + GQ_STAGE + 16384));
      prev = B_GXE - B_GQE; kc = 2;
    } else {
      mbar_wait_w(bars + 8 * (B_GQF + r.s), r.ph);
      issue(BoolC<true>{}, adesc(), bdesc(0));
      prev = r.s; r.next<GQ_N>();
      if (pending) { bar_sync<160>(NB_GSLOT); store_part(0); }
    }
#pragma unroll 1
    for (; kc < 10; kc++) {
      const uint32_t fb = bars + 8 * (B_GQF + r.s);
      bool held = true;
      if (!__all_sync(0xffffffffu, mbar_test(fb, r.ph))) {
        wg_wait<0>(); release(prev); held = false;
        mbar_wait_slow_w(fb, r.ph);
      }
      issue(BoolC<false>{}, adesc(), bdesc(kc));
      wg_wait<1>();
      if (held) release(prev);
      prev = r.s; r.next<GQ_N>();
      if (pending) {
        if (kc == 1) store_part(1);
        else { store_part(2); bar_arrive<160>(NB_GDONE); pending = false; }
      }
    }
    wg_wait<0>();
    reg_fence(d[0]); reg_fence(d[1]);
    release(prev);
    if (h + 2 >= NH && lane < 2) mbar_arrive_cluster(bars + 8 * B_QPH, lane);
    const int tile = tile_id(h, b);
    dst = tile_step(tile, warp, tile_pol(c, tile)) + lane * 4;
#pragma unroll
    for (int i = 0; i < 48; i++) pk[i] = pack_bf16(d[i / 24][2 * (i % 24)], d[i / 24][2 * (i % 24) + 1]);
    if (h >= p.n_local / NB + 2 && h + 2 < NH) pending = true;
    else {
      bar_sync<160>(NB_GSLOT);
      store_part(0); store_part(1); store_part(2);
      bar_arrive<160>(NB_GDONE);
    }
  }
}

__device__ __forceinline__ void go_wproducer(const Params& p, const Ctx& c) {
  const uint32_t sb = c.sb, bars = sb + MISC_BAR;
  const int sub = c.idx & 1, j = c.idx * 2 + c.rank;
  auto prefetch = [&](int h) { if (h < NH && elect_one()) bulk_prefetch(p.wop[c.br] + (size_t)(h * 32 + j) * 5120, 5120); };
  Ring r{0, 1};
  {
    uint32_t t_next = (uint32_t)globaltimer_ns() + WO_T0;
#pragma unroll 1
    for (int k = 0; k < 20; k++) {
      while ((int32_t)((uint32_t)globaltimer_ns() - t_next) < 0) __nanosleep(40);
      t_next += WO_DT;
      if (elect_one()) bulk_prefetch(p.wqp[c.br] + (size_t)(j + 32 * k) * (NH * DH * 2) + 4 * DH * 2, (WQ_G0 - 4) * DH * 2);
      if (k < WO_N) prefetch(k);
    }
  }
  mbar_wait_slow_w(bars + 8 * B_GXE, 0);
#pragma unroll 1
  for (int i = 0; i < 128; i++) {
    const uint32_t st = r.s;
    if (i == GO_SWITCH + GO_N) mbar_wait_slow_w(bars + 8 * B_QPH, 0);
    mbar_wait_slow_w(bars + 8 * (B_GOE + st), r.ph);
    r.next_o(i);
    if (elect_one()) {
      mbar_expect_tx(bars + 8 * (B_GOF + st), GO_STAGE);
      tma3d_mc(sb + G_O + st * GO_STAGE + c.rank * 10240, &p.wo[c.br], 0, i * 32 + c.rank * 16, sub * 5, bars + 8 * (B_GOF + st));
    }
    if ((i & 3) == 0 && i <= GO_SWITCH - 4 * GO_PF) {
      if ((i >> 2) + GO_PF >= WO_N) prefetch((i >> 2) + GO_PF);
      if (i == GO_SWITCH - 4 * GO_PF) { for (int h = GO_SWITCH / 4 + 1; h < NH; h++) prefetch(h); }
    }
  }
}

__device__ __forceinline__ void go_oproducer(const Params& p, const Ctx& c) {
  const uint32_t sb = c.sb, bars = sb + MISC_BAR;
  const int lane = threadIdx.x & 31;
  const int b = (c.idx >> 1) * 2 + c.rank;
  int ready = 0;
  Ring r{0, 1};
  auto poll = [&]() {
    bool ok = false;
    if (lane < 4 && ready + lane < NH)
      ok = (int32_t)(ld_acquire(tile_flag(c, tile_id(ready + lane, b), FL_O)) - (c.seq0 + ready + lane)) >= 0;
    ready += __ffs(~__ballot_sync(0xffffffffu, ok)) - 1;
    __syncwarp();
    fence_async_global();
  };
  mbar_wait_slow_w(bars + 8 * B_GXE, 0);
  for (int h = 0; h < NH; h++) {
    const int tile = tile_id(h, b);
    const CUtensorMap* qm = &p.quarter[tile_pol(c, tile)];
    const bool fast = 4 * h > GO_SWITCH;
    if (fast) mbar_wait_slow_w(bars + 8 * (B_GOE + r.s + 3), r.ph);
    uint32_t it = 0;
#pragma unroll 1
    while (h >= ready) {
      poll();
      if (++it > (1u << 22)) { die(); break; }
      if (h >= ready && !fast) __nanosleep(20);
    }
    if (fast) {
      if (elect_one()) {
#pragma unroll
        for (int q = 0; q < 4; q++) tma4d(sb + G_O + (r.s + q) * GO_STAGE + 20480, qm, tile * 4 + q, bars + 8 * (B_GOF + r.s + q));
      }
      r.ph ^= r.s >> 2; r.s ^= 4;
      continue;
    }
#pragma unroll 1
    for (int q = 0; q < 4; q++) {
      const uint32_t st = r.s;
      if (4 * h + q == GO_SWITCH + GO_N) mbar_wait_slow_w(bars + 8 * B_QPH, 0);
      if (ready == h + 1 && q == 3 && ready < NH && !__all_sync(0xffffffffu, mbar_test(bars + 8 * (B_GOE + st), r.ph))) poll();
      mbar_wait_slow_w(bars + 8 * (B_GOE + st), r.ph);
      r.next_o(4 * h + q);
      if (elect_one()) tma4d(sb + G_O + st * GO_STAGE + 20480, qm, tile * 4 + q, bars + 8 * (B_GOF + st));
    }
  }
}

template <int NT>
__device__ __forceinline__ void go_consumer(const Params& p, const Ctx& c) {
  const DescHi hi{p.hi_sw, p.hi_sw2, p.hi_img};
  const Tid T; const int warp = T.warp, lane = T.lane;
  const uint32_t sb = c.sb, bars = sb + MISC_BAR;
  const int sub = c.idx & 1, b = (c.idx >> 1) * 2 + c.rank;
  constexpr int t0 = NT == 3 ? 0 : 3;
  const uint32_t adesc = desc_sw128(sb + G_O + t0 * 2048), bdesc = desc_img(sb + G_O + 20480);
  float d[NT][48];
  uint32_t i = 0, prev = 0;
  Ring r{0, 0};
  auto release = [&](uint32_t j) { if (lane < 2) mbar_arrive_cluster(bars + 8 * (B_GOE + j), lane); };
  auto issue = [&](auto first) {
    wg_fence();
    const uint32_t off = r.s * (GO_STAGE >> 4);
#pragma unroll
    for (int kk = 0; kk < 2; kk++)
#pragma unroll
      for (int t = 0; t < NT; t++) {
        if (decltype(first)::value && kk == 0) wgmma96_first<1, 1>(d[t], adesc + off + ((t * 2048) >> 4), bdesc + off, hi);
        else wgmma96<1, 1>(d[t], adesc + off + ((kk * 10240 + t * 2048) >> 4), bdesc + off + ((kk * KSTEP) >> 4), 1, hi);
      }
    wg_commit();
    i++;
  };
  mbar_wait_slow_w(bars + 8 * B_GOF, 0);
  issue(BoolC<true>{});
  r.next_o(0);
#pragma unroll 1
  do {
    const uint32_t fb = bars + 8 * (B_GOF + r.s);
    bool held = true;
    if (!__all_sync(0xffffffffu, mbar_test(fb, r.ph))) {
      wg_wait<0>(); release(prev); held = false;
      mbar_wait_slow_w(fb, r.ph);
    }
    issue(BoolC<false>{});
    if (NT == 2 && (i & 3) == 0 && T.t == 0) st_relaxed(tile_flag(c, tile_id(0, b), FL_DONE + sub), c.seq0 + (i >> 2) - 1);
    wg_wait<1>();
    if (held) release(prev);
    prev = r.s; r.next_o(i - 1);
  } while (i < 124);
  const uint32_t stg = sb + G_O + 4 * GO_STAGE + t0 * 12288;
  const uint32_t st_addr = stg + ((lane >> 4) * 8 + (lane & 7)) * 128 + (((warp * 2 + ((lane >> 3) & 1)) ^ (lane & 7)) << 4);
#pragma unroll
  for (int t = 0; t <= NT; t++) {
    if (t < NT) {
#pragma unroll
      for (int q = 0; q < 4; q++) {
        if (t == 0) mbar_wait_w(bars + 8 * (B_GOF + q), r.ph);
        if (t == 0 || q == 0) wg_fence();
#pragma unroll
        for (int kk = 0; kk < 2; kk++)
          wgmma96<1, 1>(d[t], adesc + ((q * GO_STAGE + kk * 10240 + t * 2048) >> 4), bdesc + ((q * GO_STAGE + kk * KSTEP) >> 4), 1, hi);
      }
      wg_commit();
    }
    if (t > 0) {
      if (t < NT) wg_wait<1>(); else wg_wait<0>();
      reg_fence(d[t - 1]);
      if (t == 1) bar_sync<256>(NB_GEPI);
#pragma unroll
      for (int g = 0; g < 6; g++) {
        const float* e = &d[t - 1][8 * g];
        stsm4_t(st_addr + (t - 1) * 12288 + g * 2048, pack_bf16(e[0], e[1]), pack_bf16(e[2], e[3]), pack_bf16(e[4], e[5]), pack_bf16(e[6], e[7]));
      }
      fence_async_smem();
      bar_sync<128>(NB_GWG + (NT == 3 ? 0 : 1));
      if (T.t == 0) tma2d_store(&p.out, c.br * DM + sub * 320 + (t0 + t - 1) * 64, b * SQ, stg + (t - 1) * 12288);
    }
  }
  if (T.t == 0) { bulk_commit(); bulk_wait_read(); }
}

__device__ __forceinline__ uint32_t timed_atomic(uint32_t* p) {
  uint32_t t0, t1, v;
  asm volatile("mov.u32 %0, %%clock; atom.global.exch.b32 %1, [%2], %0;" : "=&r"(t0), "=r"(v) : "l"(p) : "memory");
  asm volatile("{.reg .pred q; setp.ne.u32 q, %1, %2; mov.u32 %0, 0; @q mov.u32 %0, %%clock;}" : "=r"(t1) : "r"(v), "r"(t0) : "memory");
  return t1 - t0;
}

__global__ void __cluster_dims__(2, 1, 1) __launch_bounds__(NTHREADS, 1)
fused_attn_kernel(const __grid_constant__ Params p) {
  extern __shared__ __align__(1024) unsigned char smem[];
  const uint32_t sb = smem_u32(smem);
  const int tid = threadIdx.x, wi = __shfl_sync(0xffffffffu, tid >> 5, 0), lane = tid & 31;
  const int cid = blockIdx.x >> 1, rank = blockIdx.x & 1;
  const uint32_t bars = sb + MISC_BAR;

  uint32_t epoch = 0;
  uint32_t rel0 = 0;
  if (tid == 0 && rank == 0) {
    epoch = (uint32_t)(*reinterpret_cast<volatile unsigned long long*>(&g_ticket) >> 40);
    rel0 = *reinterpret_cast<volatile uint32_t*>(&g_rel);
  }
  if (lane == 0) {
#pragma unroll
    for (int j = 0; j < 4; j++) {
      const int i = wi * 4 + j;
      const uint32_t cnt = (i >= B_EMPTY2 || (i >= B_EMPTY && i < B_QF) || (i >= B_ODONE && i < B_FULL2)) ? 4 : (i >= B_GOE && i < B_GOE + 8) ? 16
                         : (i >= B_GQE && i < B_GOF) ? 8 : 1;
      mbar_init(bars + 8 * i, cnt);
    }
    if (wi == B_SEAT / 4) mbar_expect_tx(bars + 8 * B_SEAT, 8);
    asm volatile("fence.mbarrier_init.release.cluster;" ::: "memory");
    if (wi < 15) asm volatile("prefetch.tensormap [%0];" ::"l"(&p.x[0] + wi) : "memory");
  }
  __syncwarp();
  asm volatile("barrier.cluster.arrive.relaxed.aligned;" ::: "memory");
  const uint32_t poff = blockIdx.x * 8192 + KSTEP;
  if (const int pg = wi >> 1; pg < N_PAGES && rank == 0) {
    uint32_t* pa = reinterpret_cast<uint32_t*>(scratch_base() + ((size_t)pg << 21) + poff + (wi & 1) * 4096);
    if (lane < 8) pa[lane] = 0;
    __syncwarp();
    if (lane == 0) {
      uint32_t tm = 0xffffffffu;
#pragma unroll 1
      for (int r = 0; r < PROBE_N; r++) tm = min(tm, timed_atomic(pa));
      sts32(sb + MISC + 8 * pg + 4 * (wi & 1), tm);
    }
    __syncwarp();
  }
  if (rank == 1 && wi == 1) {
    const uint64_t pol = policy_evict_first();
    uint32_t t_next = (uint32_t)globaltimer_ns();
#pragma unroll 1
    for (int step = 0; step < 8 + ST_KV; step++) {
      while ((int32_t)((uint32_t)globaltimer_ns() - t_next) < 0) __nanosleep(20);
      if (step < 8) {
        const int j = step * p.n_clusters + cid, br = j & 1, r = j >> 1, kc = r / 24, i = r % 24;
        if (kc < 10 && elect_one()) {
          if (i < 16) tma2d_prefetch(&p.x[br], kc * 64, i * SQ);
          else tma2d_prefetch(&p.wq[br], (i - 16) * 64, kc * 64);
        }
        if (step >= ST_BURST) t_next += ST_DT1;
      } else {
        const int q = step - 8, item = cid >> 1;
        if (item < p.n_local && elect_one())
          tma3d_prefetch_pol(((q & 1) ? p.v : p.k) + (cid & 1), 0, ((item & 15) * NH + (item >> 4)) * SK + 64 * (((q >> 1) + 4 * (cid & 1)) & 7), 0, pol);
        t_next += ST_DT2;
      }
    }
  }
  asm volatile("barrier.cluster.wait.aligned;" ::: "memory");
  if (rank == 0) __syncthreads();
  if (wi == 0 && rank == 0) {
    const int ta = lds32(sb + MISC + 8 * (lane & 7)), tb = lds32(sb + MISC + 8 * (lane & 7) + 4);
    const uint32_t near = __ballot_sync(0xffffffffu, lane < N_PAGES && tb < ta);
    const bool clean = __all_sync(0xffffffffu, lane >= N_PAGES || (4 * max(ta, tb) > 5 * min(ta, tb) && 2 * max(ta, tb) < 5 * min(ta, tb)));
    if (lane == 0) {
      uint32_t side = chunk_par(poff) ^ (near & 1);
      uint32_t rel = (((epoch + 1) & 0xffffff) << 8) | ((near & 1) ? ~near & 255 : near);
      if (!clean) {
        for (int i = 0; i < 4 && ((rel0 ^ rel) >> 8); i++) rel0 = *reinterpret_cast<volatile uint32_t*>(&g_rel);
      }
      if (!((rel0 ^ rel) >> 8)) rel = rel0;
      uint32_t won;
      asm volatile("atom.relaxed.gpu.global.cas.b32 %0, [%1], %2, %3;" : "=r"(won) : "l"(&g_rel), "r"(rel0), "r"(rel));
      const uint32_t att = ((cid + 4) >> 3) & 1;
      unsigned long long t = atomicAdd(&g_ticket, 1ull << (16 * side + 8 * att));
      uint32_t cg = (t >> (16 * side)) & 255, ca = (t >> (16 * side + 8)) & 255;
      if ((int)(cg + ca) >= p.half) {
        side ^= 1;
        t = atomicAdd(&g_ticket, 1ull << (16 * side + 8 * att));
        cg = (t >> (16 * side)) & 255; ca = (t >> (16 * side + 8)) & 255;
      }
      if (won != rel0) rel = won;
      const uint32_t seat = (int)(cg + ca) >= p.half ? 39 : att ? p.half - 1 - ca : cg;
#pragma unroll
      for (int r = 0; r < 2; r++)
        asm volatile("{.reg .b32 ra, rb; mapa.shared::cluster.u32 ra, %0, %4; mapa.shared::cluster.u32 rb, %1, %4;\n"
                     "st.async.shared::cluster.mbarrier::complete_tx::bytes.v2.u32 [ra], {%2, %3}, [rb];}"
                     ::"r"(sb + MISC + 128), "r"(bars + 8 * B_SEAT), "r"(((rel & 255) << 16) | (side << 8) | seat), "r"(epoch), "r"(r) : "memory");
      t = atomicAdd(&g_ticket, 1ull << 32);
      if ((int)((t >> 32) & 255) == p.n_clusters - 1) {
        for (int i = 0; i < 2; i++) g_prog[(((epoch + 1) & 1) * 2 + i) * 32] = 0;
        atomicExch(&g_ticket, (unsigned long long)((epoch + 1) & 0xffffff) << 40);
      }
    }
    __syncwarp();
  }
  mbar_wait_slow_w(bars + 8 * B_SEAT, 0);
  Ctx c;
  c.sb = sb; c.rank = rank;
  const int pos = __shfl_sync(0xffffffffu, lds32(sb + MISC + 128), 0);
  c.seq0 = __shfl_sync(0xffffffffu, lds32(sb + MISC + 132), 0) * NH + 1;
  c.pol = pos >> 16;
  c.br = (pos >> 8) & 1;
  const int k = pos & 255;
  const int role = p.role[k];
  c.idx = p.idx[k];

  const int a = c.idx * 2 + rank;
  const int n_items = p.items_base + (a < p.items_extra);
  if (wi >= 12) {
    asm volatile("setmaxnreg.dec.sync.aligned.u32 32;");
    const int pw = wi - 12;
    if (role == ROLE_ATT) {
      if (pw == 1) att_qloader(p, c, a, n_items);
      else if (pw == 2) att_flags(p, c, a, n_items);
      else att_producer(p, c, a, n_items, pw == 3);
    } else if (role == ROLE_G) {
      if (pw == 0) gq_producer(p, c);
      else if (pw == 1) go_oproducer(p, c);
      else if (pw == 2) gq_flags(p, c);
      else go_wproducer(p, c);
    }
    asm volatile("barrier.cluster.arrive.relaxed.aligned; barrier.cluster.wait.aligned; // producer" ::: "memory");
  } else if (wi >= 8) {
    if (role == ROLE_ATT) att_pv_wg(p, c, a, n_items);
    else if (role == ROLE_G) go_consumer<2>(p, c);
    asm volatile("barrier.cluster.arrive.relaxed.aligned; barrier.cluster.wait.aligned; // wg2" ::: "memory");
  } else {
    asm volatile("setmaxnreg.inc.sync.aligned.u32 176;");
    if (role == ROLE_ATT) att_softmax_wg(p, sb, n_items);
    else if (role == ROLE_G) { if (wi < 4) go_consumer<3>(p, c); else gq_consumer(p, c); }
    asm volatile("barrier.cluster.arrive.relaxed.aligned; barrier.cluster.wait.aligned; // consumer" ::: "memory");
  }
}

typedef CUresult (*EncodeFn)(CUtensorMap*, CUtensorMapDataType, cuuint32_t, void*, const cuuint64_t*, const cuuint64_t*,
                             const cuuint32_t*, const cuuint32_t*, CUtensorMapInterleave, CUtensorMapSwizzle,
                             CUtensorMapL2promotion, CUtensorMapFloatOOBfill);

void encode(EncodeFn enc, CUtensorMap* m, void* ptr, int rank, const cuuint64_t* dims, const cuuint64_t* strides, const cuuint32_t* box) {
  cuuint32_t es[3] = {1, 1, 1};
  enc(m, CU_TENSOR_MAP_DATA_TYPE_BFLOAT16, rank, ptr, dims, strides, box, es, CU_TENSOR_MAP_INTERLEAVE_NONE,
      CU_TENSOR_MAP_SWIZZLE_128B, CU_TENSOR_MAP_L2_PROMOTION_L2_128B, CU_TENSOR_MAP_FLOAT_OOB_FILL_NONE);
}

}

extern "C" void kernel_launch(void* const* d_in, const int* in_sizes, int n_in, void* d_out, int out_size) {
  (void)in_sizes; (void)n_in; (void)out_size;
  static EncodeFn enc = nullptr;
  static int n_clusters = 0;
  if (!enc) {
    cudaDriverEntryPointQueryResult qr;
    cudaGetDriverEntryPoint("cuTensorMapEncodeTiled", (void**)&enc, cudaEnableDefault, &qr);
    cudaFuncSetAttribute(fused_attn_kernel, cudaFuncAttributeMaxDynamicSharedMemorySize, SMEM_BYTES);
    cudaLaunchConfig_t cfg = {};
    cfg.gridDim = dim3(128); cfg.blockDim = dim3(NTHREADS); cfg.dynamicSmemBytes = SMEM_BYTES;
    cudaLaunchAttribute at[1];
    at[0].id = cudaLaunchAttributeClusterDimension; at[0].val.clusterDim.x = 2; at[0].val.clusterDim.y = 1; at[0].val.clusterDim.z = 1;
    cfg.attrs = at; cfg.numAttrs = 1;
    int mx = 0;
    cudaOccupancyMaxActiveClusters(&mx, fused_attn_kernel, &cfg);
    n_clusters = mx < 66 ? mx : 66;
    if (n_clusters < 34) n_clusters = 34;
  }
  Params p;
  for (int br = 0; br < 2; br++) {
    void* x = d_in[5 * br + 0]; void* k = d_in[5 * br + 1]; void* v = d_in[5 * br + 2];
    void* wq = d_in[5 * br + 3]; void* wo = d_in[5 * br + 4];
    p.wqp[br] = (const unsigned char*)wq; p.wop[br] = (const unsigned char*)wo;
    p.kp[br] = (const __nv_bfloat16*)k; p.vp[br] = (const __nv_bfloat16*)v;
    { cuuint64_t d[2] = {DM, NB * SQ}, s[1] = {DM * 2}; cuuint32_t bx[2] = {64, SQ}; encode(enc, &p.x[br], x, 2, d, s, bx); }
    { cuuint64_t d[2] = {NH * DH, DM}, s[1] = {NH * DH * 2}; cuuint32_t bx[2] = {64, 64}; encode(enc, &p.wq[br], wq, 2, d, s, bx); }
    { cuuint64_t d[3] = {64, NB * NH * SK, 2}, s[2] = {DH * 2, 128}; cuuint32_t bx[3] = {64, 64, 2};
      encode(enc, &p.k[br], k, 3, d, s, bx); encode(enc, &p.v[br], v, 3, d, s, bx); }
    { cuuint64_t d[3] = {64, NH * DH, 10}, s[2] = {DM * 2, 128}; cuuint32_t bx[3] = {64, 16, 5}; encode(enc, &p.wo[br], wo, 3, d, s, bx); }
  }
  { cuuint64_t d[2] = {2 * DM, NB * SQ}, s[1] = {2 * DM * 2}; cuuint32_t bx[2] = {64, SQ}; encode(enc, &p.out, d_out, 2, d, s, bx); }
  {
    void* raw = nullptr;
    cudaGetSymbolAddress(&raw, g_scratch_raw);
    char* base = (char*)(((uintptr_t)raw + (1u << 21) - 1) & ~(uintptr_t)((1u << 21) - 1));
    for (int pl = 0; pl < 2; pl++) {
      cuuint64_t d[4] = {192, 2, 2, (cuuint64_t)N_PAGES * 128}, st[3] = {1536, pl ? 4096u : 12288u, 16384};
      cuuint32_t es[4] = {1, 1, 1, 1}, bt[4] = {192, 2, 2, 4}, bq[4] = {192, 2, 2, 1};
      enc(&p.tile[pl], CU_TENSOR_MAP_DATA_TYPE_INT64, 4, base + pl * 4096, d, st, bt, es, CU_TENSOR_MAP_INTERLEAVE_NONE,
          CU_TENSOR_MAP_SWIZZLE_NONE, CU_TENSOR_MAP_L2_PROMOTION_NONE, CU_TENSOR_MAP_FLOAT_OOB_FILL_NONE);
      enc(&p.quarter[pl], CU_TENSOR_MAP_DATA_TYPE_INT64, 4, base + pl * 4096, d, st, bq, es, CU_TENSOR_MAP_INTERLEAVE_NONE,
          CU_TENSOR_MAP_SWIZZLE_NONE, CU_TENSOR_MAP_L2_PROMOTION_NONE, CU_TENSOR_MAP_FLOAT_OOB_FILL_NONE);
    }
  }
  p.hi_sw = p.hi_sw2 = SW128_HI; p.hi_img = IMG_HI;
  p.n_clusters = n_clusters; p.half = n_clusters / 2;
  const int att_cl = p.half - 16 < ATT_CL ? p.half - 16 : ATT_CL;
  p.n_att = 2 * att_cl;
  p.items_base = NB * NH / p.n_att; p.items_extra = NB * NH % p.n_att;
  p.n_local = p.n_att >= 2 * NB ? 2 * NB : 0;
  for (int k = 0; k < 40; k++) {
    p.role[k] = k < 16 ? ROLE_G : (k < p.half && p.half - 1 - k < att_cl) ? ROLE_ATT : ROLE_NONE;
    p.idx[k] = (unsigned char)(k < 16 ? k : k < p.half ? p.half - 1 - k : 0);
  }
  fused_attn_kernel<<<2 * n_clusters, NTHREADS, SMEM_BYTES, cudaStreamPerThread>>>(p);
}
```
